```python
import torch

def _softmax(x, axis=-1):
    return torch.softmax(x, dim=axis)
def _gelu(x):
    return torch.nn.functional.gelu(x, approximate="tanh")
def _silu(x):
    return torch.nn.functional.silu(x)
def _sigmoid(x):
    return torch.sigmoid(x)
def _layernorm(x, axis=-1, eps=1e-5):
    m = x.mean(dim=axis, keepdim=True)
    v = x.var(dim=axis, keepdim=True, unbiased=False)
    return (x - m) / torch.sqrt(v + eps)
def _scatter_add(tgt, idx, src, axis=0):
    return tgt.clone().index_add_(axis, idx, src)
def _segment_sum(src, seg, n):
    out = torch.zeros((n,) + src.shape[1:], dtype=src.dtype)
    return out.index_add_(0, seg, src)
def _pad(x, pw):
    flat = tuple(v for pair in reversed(pw) for v in pair)
    return torch.nn.functional.pad(x, flat)

kernel_name = 'sequential_preLN__sliding_block_cached__dense_activation_relu__decode'

def setup_inputs():

    _w = (lambda a: (lambda t: t.to(torch.bfloat16) if t.is_floating_point() else t)(torch.as_tensor(a)))
    def _A_setup():
        B, Sq, D = 1, 1, 640
        Hq, Hkv, Sk, Dh = 32, 32, 4096, 128
        assert Hq % Hkv == 0, (Hq, Hkv)
        return {
            "x": _w((lambda *s: torch.randn(*s, dtype=torch.bfloat16) * 0.05)(B, Sq, D)),
            "k_cache": _w((lambda *s: torch.randn(*s, dtype=torch.bfloat16) * 3.2)(B, Hkv, Sk, Dh)),
            "v_cache": _w((lambda *s: torch.randn(*s, dtype=torch.bfloat16) * 0.4)(B, Hkv, Sk, Dh)),
            "wq": _w((lambda *s: torch.randn(*s, dtype=torch.bfloat16) * 3.2)(D, Hq * Dh) * (D ** -0.5)),
            "wo": _w((lambda *s: torch.randn(*s, dtype=torch.bfloat16) * 0.4)(Hq * Dh, D) * ((Hq * Dh) ** -0.5)),
        }
    _A_in = _A_setup()

    def _B_setup():
        B, S, D, Dff = 1, 1, 640, 1728
        return {
            "x": _w((lambda *s: torch.randn(*s, dtype=torch.bfloat16) * 0.05)(B, S, D)),
            "w1": _w((lambda *s: torch.randn(*s, dtype=torch.bfloat16) * 0.05)(D, Dff)),
            "w2": _w((lambda *s: torch.randn(*s, dtype=torch.bfloat16) * 0.05)(Dff, D)),
        }
    _B_in = _B_setup()

    return {
        "A_x": _A_in["x"],
        "A_k_cache": _A_in["k_cache"],
        "A_v_cache": _A_in["v_cache"],
        "A_wq": _A_in["wq"],
        "A_wo": _A_in["wo"],
        "B_x": _B_in["x"],
        "B_w1": _B_in["w1"],
        "B_w2": _B_in["w2"],
    }

def reference(A_x, A_k_cache, A_v_cache, A_wq, A_wo, B_x, B_w1, B_w2):
    def _A_ref(x, k_cache, v_cache, wq, wo):
        B, Sq, D = x.shape
        Hq, Dh = 32, 128
        Hkv, Sk = k_cache.shape[1], k_cache.shape[2]
        W = min(4096, max(256, Sk // 4))
        rep = Hq // Hkv
        q = (lambda x, *d: x.permute(*d))((x @ wq).reshape(B, Sq, Hq, Dh), 0, 2, 1, 3)
        k = (lambda x, n, axis: torch.repeat_interleave(x, n, dim=axis))(k_cache[:, :, Sk - W:, :], rep, axis=1)
        v = (lambda x, n, axis: torch.repeat_interleave(x, n, dim=axis))(v_cache[:, :, Sk - W:, :], rep, axis=1)
        scores = torch.einsum("bhqd,bhkd->bhqk", q, k) * (Dh ** -0.5)
        p = _softmax(scores, axis=-1)
        o = torch.einsum("bhqk,bhkd->bhqd", p, v)
        return (lambda x, *d: x.permute(*d))(o, 0, 2, 1, 3).reshape(B, Sq, Hq * Dh) @ wo

    def _B_ref(x, w1, w2):
        h = torch.einsum("bsd,df->bsf", x, w1)
        zero = torch.zeros_like(h)
        h = torch.maximum(h, zero)
        return torch.einsum("bsf,fd->bsd", h, w2)

    x = A_x
    h = x + _A_ref(_layernorm(x, axis=-1), A_k_cache, A_v_cache, A_wq, A_wo)
    h2 = h + _B_ref(_layernorm(h, axis=-1), B_w1, B_w2)
    return h2
```

```cpp
#include <cuda_runtime.h>
#include <cuda.h>
#include <cuda_bf16.h>
#include <stdint.h>

namespace fk {

constexpr int NCTA = 128;
constexpr int NFFN = 108;
constexpr int NOCT = 80;
constexpr int NTHREADS = 384;

constexpr int ROW_PITCH = 1296;
constexpr int SM_K = 0;
constexpr int SM_V = 65536;
constexpr int SM_W1 = 131072;
constexpr int SM_WO = SM_W1 + 640 * 32;
constexpr int SM_W2 = SM_WO + 32 * ROW_PITCH;
constexpr int SM_QPART = SM_W2 + 16 * ROW_PITCH;
constexpr int SM_P = SM_QPART + 5120;
constexpr int SM_XN = SM_P + 2048;
constexpr int SM_OPART = SM_XN + 2560;
constexpr int SM_ML = SM_OPART + 1024;
constexpr int SM_QS = SM_ML + 64;
constexpr int SM_CSP = SM_QS + 256;
constexpr int SM_DP = SM_CSP + 768;
constexpr int SM_FSTAT = SM_DP + 768;
constexpr int SM_TAG = SM_FSTAT + 96;
constexpr int SM_BAR = SM_TAG + 32;
constexpr int BAR_K = 0, BAR_V = 16, BAR_WO = 32, BAR_W1 = 34, BAR_W2 = 39, NBAR = 40;
constexpr int SMEM_BYTES = SM_BAR + NBAR * 8;

constexpr int SPIN_LIMIT = 1 << 20;

struct Pace {
    int tK;
    int dKV;
    int dWO;
    int dW1;
    int dW2;
    int stag;
    int dlyD;
    int prew;
    int mode;
    int dlyH;
    int tC;
    int order;
    int gap;
    int sV;
};

__device__ unsigned g_epoch;
__device__ __align__(128) unsigned g_xa[NCTA * 128];
__device__ __align__(128) unsigned g_xs[32 * 1024];
__device__ __align__(128) unsigned g_xc1[NOCT * NCTA * 8];
__device__ __align__(128) unsigned g_xc2[4 * 640];
__device__ __align__(128) unsigned g_xd[NOCT * NCTA * 8];
#define TL(i) do {} while (0)
#define TLD(i, v) do {} while (0)
#define TLV(i, v) do {} while (0)

__device__ __forceinline__ unsigned gtime32() {
    unsigned t; asm volatile("mov.u32 %0, %globaltimer_lo;" : "=r"(t) :: "memory"); return t;
}
__device__ __forceinline__ uint32_t smem_u32(const void* p) { return (uint32_t)__cvta_generic_to_shared(p); }
__device__ __forceinline__ void mbar_init(uint32_t bar, uint32_t cnt) {
    asm volatile("mbarrier.init.shared::cta.b64 [%0], %1;" :: "r"(bar), "r"(cnt) : "memory");
}
__device__ __forceinline__ void mbar_expect_tx(uint32_t bar, uint32_t bytes) {
    asm volatile("mbarrier.arrive.expect_tx.shared::cta.b64 _, [%0], %1;" :: "r"(bar), "r"(bytes) : "memory");
}
__device__ __forceinline__ bool mbar_try(uint32_t bar) {
    uint32_t ok;
    asm volatile("{\n.reg .pred p;\nmbarrier.try_wait.parity.shared::cta.b64 p, [%1], 0;\nselp.u32 %0, 1, 0, p;\n}"
                 : "=r"(ok) : "r"(bar) : "memory");
    return ok != 0;
}
__device__ __forceinline__ void mbar_wait(uint32_t bar) {
#pragma unroll 1
    for (int n = 0; n < SPIN_LIMIT; n++) if (mbar_try(bar)) break;
}
__device__ __forceinline__ void bulk_g2s(uint32_t dst, const void* src, uint32_t bytes, uint32_t bar) {
    asm volatile("cp.async.bulk.shared::cluster.global.mbarrier::complete_tx::bytes [%0], [%1], %2, [%3];"
                 :: "r"(dst), "l"(src), "r"(bytes), "r"(bar) : "memory");
}
__device__ __forceinline__ void tma2d(uint32_t dst, const CUtensorMap* map, int c0, int c1, uint32_t bar) {
    asm volatile("cp.async.bulk.tensor.2d.shared::cluster.global.mbarrier::complete_tx::bytes [%0], [%1, {%3, %4}], [%2];"
                 :: "r"(dst), "l"(map), "r"(bar), "r"(c0), "r"(c1) : "memory");
}
__device__ __forceinline__ uint4 ldg_nc16(const void* p) {
    uint4 v;
    asm volatile("ld.global.nc.L1::no_allocate.v4.u32 {%0,%1,%2,%3}, [%4];"
                 : "=r"(v.x), "=r"(v.y), "=r"(v.z), "=r"(v.w) : "l"(p));
    return v;
}
__device__ __forceinline__ uint2 ldg_nc8(const void* p) {
    uint2 v;
    asm volatile("ld.global.nc.v2.u32 {%0,%1}, [%2];" : "=r"(v.x), "=r"(v.y) : "l"(p));
    return v;
}
__device__ __forceinline__ unsigned tagw(float v, unsigned tag) { return (__float_as_uint(v) & ~3u) | tag; }
__device__ __forceinline__ float untag(unsigned w) { return __uint_as_float(w & ~3u); }
__device__ __forceinline__ void st_w1(unsigned* p, unsigned a) {
    asm volatile("st.relaxed.gpu.global.u32 [%0], %1;" :: "l"(p), "r"(a) : "memory");
}
__device__ __forceinline__ void st_w4(unsigned* p, uint4 v) {
    asm volatile("st.relaxed.gpu.global.v4.u32 [%0], {%1,%2,%3,%4};" :: "l"(p), "r"(v.x), "r"(v.y), "r"(v.z), "r"(v.w) : "memory");
}
__device__ __forceinline__ uint2 ld_w2(const unsigned* p) {
    uint2 v;
    asm volatile("ld.relaxed.gpu.global.v2.u32 {%0,%1}, [%2];" : "=r"(v.x), "=r"(v.y) : "l"(p) : "memory");
    return v;
}
__device__ __forceinline__ uint4 ld_w4(const unsigned* p) {
    uint4 v;
    asm volatile("ld.relaxed.gpu.global.v4.u32 {%0,%1,%2,%3}, [%4];" : "=r"(v.x), "=r"(v.y), "=r"(v.z), "=r"(v.w) : "l"(p) : "memory");
    return v;
}
__device__ __forceinline__ bool bad2(uint2 v, unsigned tag) { return (v.x & v.y & tag) == 0; }
__device__ __forceinline__ bool bad4(uint4 v, unsigned tag) { return ((v.x & v.y & v.z) & v.w & tag) == 0; }

__device__ __forceinline__ void bar_sync(int id, int n) { __syncwarp(); asm volatile("bar.sync %0, %1;" :: "r"(id), "r"(n) : "memory"); }
__device__ __forceinline__ void bar_arrive(int id, int n) { __syncwarp(); asm volatile("bar.arrive %0, %1;" :: "r"(id), "r"(n) : "memory"); }
__device__ __forceinline__ float bf_lo(unsigned u) { return __uint_as_float(u << 16); }
__device__ __forceinline__ float bf_hi(unsigned u) { return __uint_as_float(u & 0xffff0000u); }
__device__ __forceinline__ unsigned pack_bf(float lo, float hi) {
    unsigned r; asm("cvt.rn.bf16x2.f32 %0, %1, %2;" : "=r"(r) : "f"(hi), "f"(lo)); return r;
}
__device__ __forceinline__ float bfr(float v) { return __uint_as_float(pack_bf(0.f, v)); }
__device__ __forceinline__ float selp(float a, float b, unsigned c) {
    float r; asm("{\n.reg .pred p;\nsetp.ne.u32 p, %3, 0;\nselp.f32 %0, %1, %2, p;\n}" : "=f"(r) : "f"(a), "f"(b), "r"(c)); return r;
}
__device__ __forceinline__ float sel4(float a0, float a1, float a2, float a3, int t) {
    return selp(selp(a3, a2, t & 1), selp(a1, a0, t & 1), t & 2);
}
__device__ __forceinline__ float fast_sqrt(float v) { float r; asm("sqrt.approx.f32 %0, %1;" : "=f"(r) : "f"(v)); return r; }
__device__ __forceinline__ float fast_rcp(float v) { float r; asm("rcp.approx.f32 %0, %1;" : "=f"(r) : "f"(v)); return r; }
template <class T> __device__ __forceinline__ T* pin(T* p) { asm volatile("" : "+l"(p)); return p; }
__device__ __forceinline__ void mma16816(float (&c)[4], unsigned a0, unsigned a1, unsigned a2, unsigned a3,
                                         unsigned b0, unsigned b1) {
    asm volatile("mma.sync.aligned.m16n8k16.row.col.f32.bf16.bf16.f32 {%0,%1,%2,%3}, {%4,%5,%6,%7}, {%8,%9}, {%0,%1,%2,%3};"
                 : "+f"(c[0]), "+f"(c[1]), "+f"(c[2]), "+f"(c[3])
                 : "r"(a0), "r"(a1), "r"(a2), "r"(a3), "r"(b0), "r"(b1));
}
__device__ __forceinline__ uint4 ldsm4t(uint32_t addr) {
    uint4 r;
    asm volatile("ldmatrix.sync.aligned.m8n8.x4.trans.shared.b16 {%0,%1,%2,%3}, [%4];"
                 : "=r"(r.x), "=r"(r.y), "=r"(r.z), "=r"(r.w) : "r"(addr) : "memory");
    return r;
}
__device__ __forceinline__ uint4 lds16(uint32_t addr) {
    uint4 r;
    asm volatile("ld.shared.v4.u32 {%0,%1,%2,%3}, [%4];" : "=r"(r.x), "=r"(r.y), "=r"(r.z), "=r"(r.w) : "r"(addr) : "memory");
    return r;
}
__device__ __forceinline__ void wait_until(unsigned t0, int t) {
    int n = 0;
    while ((int)(gtime32() - t0) < t && ++n < SPIN_LIMIT) {}
}
__device__ __forceinline__ float octet_reduce(float v0, float v1, float v2, float v3, int lane) {
    const unsigned FULL = 0xffffffffu;
    const unsigned b1 = lane & 2, b2 = lane & 4;
    float k0 = selp(v2, v0, b1), k1 = selp(v3, v1, b1);
    const float s0 = selp(v0, v2, b1), s1 = selp(v1, v3, b1);
    k0 += __shfl_xor_sync(FULL, s0, 2);
    k1 += __shfl_xor_sync(FULL, s1, 2);
    float k = selp(k1, k0, b2);
    const float s = selp(k0, k1, b2);
    k += __shfl_xor_sync(FULL, s, 4);
    k += __shfl_xor_sync(FULL, k, 8);
    k += __shfl_xor_sync(FULL, k, 16);
    return k;
}

__device__ __forceinline__ void spin_cycles(int n) {
    if (n > 0) { const unsigned c0 = clock(); while ((int)(clock() - c0) < n) {} }
}
template <int NSRC>
__device__ __forceinline__ float reduce_inbox(const unsigned* p, unsigned tag, int lane) {
    constexpr int NL = (NSRC + 15) / 16;
    const unsigned FULL = 0xffffffffu;
    const bool tail_on = (NSRC % 16 == 0) || (lane < 2 * (NSRC % 16));
    uint4 v[NL];
#pragma unroll
    for (int j = 0; j < NL; j++) {
        v[j] = make_uint4(tag, tag, tag, tag);
        if (j < NL - 1 || tail_on) v[j] = ld_w4(p + 128 * j);
    }
    float r = 0.f;
#pragma unroll 1
    for (int n = 0; n < SPIN_LIMIT; n++) {
        float s[4][2];
#pragma unroll
        for (int j = 0; j < NL; j++) {
            if (j < 2) {
                s[0][j] = __uint_as_float(v[j].x); s[1][j] = __uint_as_float(v[j].y); s[2][j] = __uint_as_float(v[j].z); s[3][j] = __uint_as_float(v[j].w);
            } else {
                s[0][j & 1] += __uint_as_float(v[j].x); s[1][j & 1] += __uint_as_float(v[j].y);
                s[2][j & 1] += __uint_as_float(v[j].z); s[3][j & 1] += __uint_as_float(v[j].w);
            }
        }
        float t0 = s[0][0] + s[0][1], t1 = s[1][0] + s[1][1], t2 = s[2][0] + s[2][1], t3 = s[3][0] + s[3][1];
        asm volatile("" : "+f"(t0), "+f"(t1), "+f"(t2), "+f"(t3));
        bool miss = false;
#pragma unroll
        for (int j = 0; j < NL; j++)
            if (bad4(v[j], tag)) { v[j] = ld_w4(p + 128 * j); miss = true; }
        miss = __any_sync(FULL, miss);
        r = octet_reduce(t0, t1, t2, t3, lane);
        if (!miss) break;
    }
    return r;
}

constexpr int NB_XN = 1, NB_QPART = 2, NB_Q = 3, NB_OPART = 4, NB_FPART = 5, NB_DSENT = 6, NB_C2 = 7;

__global__ void __launch_bounds__(NTHREADS, 1)
fused_decode_kernel(const __nv_bfloat16* __restrict__ x, const __nv_bfloat16* __restrict__ kc,
                    const __nv_bfloat16* __restrict__ wq, const __nv_bfloat16* __restrict__ wo,
                    const __nv_bfloat16* __restrict__ w2, __nv_bfloat16* __restrict__ out, const Pace pc,
                    const __grid_constant__ CUtensorMap map_v, const __grid_constant__ CUtensorMap map_w1) {
    extern __shared__ __align__(1024) unsigned char smem[];
    const int tid = threadIdx.x, warp = tid >> 5, lane = tid & 31;
    const int b = blockIdx.x, h = b >> 2, c = b & 3;
    const uint32_t sb = smem_u32(smem);
    const uint32_t bars = sb + SM_BAR;
    const int g = lane >> 2, t = lane & 3;
    const unsigned FULL = 0xffffffffu;

    if (warp >= 2 && warp < 12) {
        const int cw = warp - 2, ct = tid - 64;
        uint4 wr[8];
        {
            const char* wp = reinterpret_cast<const char*>(wq) + (size_t)(160 * c + (ct >> 4)) * 8192 + h * 256 + (ct & 15) * 16;
#pragma unroll
            for (int i = 0; i < 8; i++) wr[i] = ldg_nc16(wp + (size_t)i * 20 * 8192);
        }
        if (ct == 0) TL(15);
        bar_sync(NB_XN, NTHREADS);
        const unsigned tag = *reinterpret_cast<volatile unsigned*>(smem + SM_TAG);
        const int oslot = (2 * (4 * cw + t) * NCTA + b) * 8 + g;
        unsigned* const c1_dst = pin(&g_xc1[oslot]);
        unsigned* const d_dst = pin(&g_xd[oslot]);
        const unsigned* const h_src = pin(&g_xc2[c * 640 + 2 * ct]);
        unsigned* const s_dst = &g_xs[b * 256 + (cw + 8 * (t >> 1)) * 16 + 8 * (t & 1) + g];
        if (pc.prew & 2) { st_w1(c1_dst, 0u); st_w1(c1_dst + NCTA * 8, 0u); }
        if ((pc.prew & 4) && b < NFFN) { st_w1(d_dst, 0u); st_w1(d_dst + NCTA * 8, 0u); }
        if ((pc.prew & 1) && cw < 8) st_w1(s_dst, 0u);
        {
            const float* xn = reinterpret_cast<const float*>(smem + SM_XN) + 160 * c + (ct >> 4);
            float acc[8];
#pragma unroll
            for (int j = 0; j < 8; j++) acc[j] = 0.f;
#pragma unroll
            for (int i = 0; i < 8; i++) {
                const float xv = xn[20 * i];
                acc[0] = fmaf(xv, bf_lo(wr[i].x), acc[0]); acc[1] = fmaf(xv, bf_hi(wr[i].x), acc[1]);
                acc[2] = fmaf(xv, bf_lo(wr[i].y), acc[2]); acc[3] = fmaf(xv, bf_hi(wr[i].y), acc[3]);
                acc[4] = fmaf(xv, bf_lo(wr[i].z), acc[4]); acc[5] = fmaf(xv, bf_hi(wr[i].z), acc[5]);
                acc[6] = fmaf(xv, bf_lo(wr[i].w), acc[6]); acc[7] = fmaf(xv, bf_hi(wr[i].w), acc[7]);
            }
#pragma unroll
            for (int j = 0; j < 8; j++) acc[j] += __shfl_xor_sync(FULL, acc[j], 16);
            if (lane < 16) {
                float4* qp = reinterpret_cast<float4*>(smem + SM_QPART + cw * 512 + lane * 32);
                qp[0] = make_float4(acc[0], acc[1], acc[2], acc[3]);
                qp[1] = make_float4(acc[4], acc[5], acc[6], acc[7]);
            }
        }
        bar_arrive(NB_QPART, 352);
        if (pc.mode == 1) return;

        const int mi = lane >> 3, ri = lane & 7;
        if (cw < 8) {
            bar_sync(NB_Q, 288);
            uint4 qf[4];
#pragma unroll
            for (int j = 0; j < 4; j++) qf[j] = lds16(sb + SM_QS + 16 * (t + 4 * (j ^ (g & 1))));
            float mys = 0.f;
#pragma unroll 1
            for (int tile = 0; tile < 2; tile++) {
                const int ch = cw + 8 * tile;
                mbar_wait(bars + (BAR_K + ch) * 8);
                const uint32_t kb = sb + SM_K + ch * 4096 + g * 256 + t * 16;
                float cA[4] = {0.f, 0.f, 0.f, 0.f}, cB[4] = {0.f, 0.f, 0.f, 0.f};
#pragma unroll
                for (int j = 0; j < 4; j++) {
                    const uint32_t a = kb + 64 * (j ^ (g & 1));
                    const uint4 ra = lds16(a), rb = lds16(a + 2048);
                    mma16816(cA, ra.x, rb.x, ra.y, rb.y, qf[j].x, qf[j].y);
                    mma16816(cB, ra.z, rb.z, ra.w, rb.w, qf[j].z, qf[j].w);
                }
                const float s0 = selp(cA[1] + cB[1], cA[0] + cB[0], g & 1);
                const float s1 = selp(cA[3] + cB[3], cA[2] + cB[2], g & 1);
                mys = selp(selp(s1, s0, t & 1), mys, (t >> 1) == tile);
            }
            mys = bfr(bfr(mys) * 0.08838834764831845f);
            st_w1(s_dst, __float_as_uint(mys) | tag);
            if (ct == 224) TL(3);
            {
                const unsigned* ps = &g_xs[h * 1024 + (cw + 8 * (lane >> 4)) * 64 + 4 * (lane & 15)];
                mbar_wait(bars + (BAR_V + pc.sV) * 8);
                uint4 v = ld_w4(ps);
#pragma unroll 1
                for (int n = 0; n < SPIN_LIMIT; n++) {
                    if (!__any_sync(FULL, bad4(v, tag))) break;
                    __nanosleep(200);
                    v = ld_w4(ps);
                }
                if (ct == 224) TL(28);
                const float e0 = untag(v.x), e1 = untag(v.y), e2 = untag(v.z), e3 = untag(v.w);
                float m = fmaxf(fmaxf(e0, e1), fmaxf(e2, e3));
#pragma unroll
                for (int o = 16; o; o >>= 1) m = fmaxf(m, __shfl_xor_sync(FULL, m, o));
                const unsigned p01 = pack_bf(__expf(e0 - m), __expf(e1 - m)), p23 = pack_bf(__expf(e2 - m), __expf(e3 - m));
                reinterpret_cast<uint2*>(smem + SM_P)[cw * 32 + lane] = make_uint2(p01, p23);
                float l = (bf_lo(p01) + bf_hi(p01)) + (bf_lo(p23) + bf_hi(p23));
#pragma unroll
                for (int o = 16; o; o >>= 1) l += __shfl_xor_sync(FULL, l, o);
                if (lane == 0) reinterpret_cast<float2*>(smem + SM_ML)[cw] = make_float2(m, l);
                __syncwarp();
                if (ct == 224) TL(5);
            }
            float o0[4] = {0.f, 0.f, 0.f, 0.f}, o1[4] = {0.f, 0.f, 0.f, 0.f};
            const int vrow = (mi >> 1) * 8 + ri;
            const uint32_t va0 = vrow * 64 + (((mi & 1) ^ ((ri >> 1) & 3)) * 16);
            const uint32_t va1 = vrow * 64 + (((2 + (mi & 1)) ^ ((ri >> 1) & 3)) * 16);
#pragma unroll 1
            for (int tile = 0; tile < 2; tile++) {
                const int ch = cw + 8 * tile;
                const unsigned* pp = reinterpret_cast<const unsigned*>(smem + SM_P) + cw * 64 + tile * 32 + t;
                unsigned pf[8];
#pragma unroll
                for (int s = 0; s < 8; s++) pf[s] = pp[4 * s];
                mbar_wait(bars + (BAR_V + ch) * 8);
                const uint32_t vb = sb + SM_V + ch * 4096;
#pragma unroll
                for (int s = 0; s < 4; s++) {
                    const uint4 a0 = ldsm4t(vb + s * 1024 + va0), a1 = ldsm4t(vb + s * 1024 + va1);
                    mma16816(o0, a0.x, a0.y, a0.z, a0.w, pf[2 * s], pf[2 * s + 1]);
                    mma16816(o1, a1.x, a1.y, a1.z, a1.w, pf[2 * s], pf[2 * s + 1]);
                }
            }
            reinterpret_cast<float*>(smem + SM_OPART)[cw * 32 + 8 * t + g] = sel4(o0[0], o0[2], o1[0], o1[2], t);
        }
        bar_sync(NB_OPART, 320);

        const uint32_t rowoff = ((mi >> 1) * 8 + ri) * ROW_PITCH + cw * 128 + (mi & 1) * 16;
        {
            const float* op = reinterpret_cast<const float*>(smem + SM_OPART) + lane;
            const float4* ml = reinterpret_cast<const float4*>(smem + SM_ML);
            const float4 e0 = ml[0], e1 = ml[1], e2 = ml[2], e3 = ml[3];
            const float M = fmaxf(fmaxf(fmaxf(e0.x, e0.z), fmaxf(e1.x, e1.z)), fmaxf(fmaxf(e2.x, e2.z), fmaxf(e3.x, e3.z)));
            const float f0 = __expf(e0.x - M), f1 = __expf(e0.z - M), f2 = __expf(e1.x - M), f3 = __expf(e1.z - M);
            const float f4 = __expf(e2.x - M), f5 = __expf(e2.z - M), f6 = __expf(e3.x - M), f7 = __expf(e3.z - M);
            const float l = ((f0 * e0.y + f1 * e0.w) + (f2 * e1.y + f3 * e1.w)) + ((f4 * e2.y + f5 * e2.w) + (f6 * e3.y + f7 * e3.w));
            float o = ((f0 * op[0] + f1 * op[32]) + (f2 * op[64] + f3 * op[96])) + ((f4 * op[128] + f5 * op[160]) + (f6 * op[192] + f7 * op[224]));
            o *= fast_rcp(l);
            if (ct == 0) TLD(4, o);
            const unsigned pr = pack_bf(o, __shfl_down_sync(FULL, o, 1));
            unsigned bf[4];
#pragma unroll
            for (int s = 0; s < 4; s++) bf[s] = __shfl_sync(FULL, pr, 8 * s + 2 * t);
            float y[4][4];
#pragma unroll
            for (int j = 0; j < 4; j++) y[j][0] = y[j][1] = y[j][2] = y[j][3] = 0.f;
#pragma unroll
            for (int s = 0; s < 2; s++) {
                mbar_wait(bars + (BAR_WO + s) * 8);
                uint4 a[4];
#pragma unroll
                for (int j = 0; j < 4; j++) a[j] = ldsm4t(sb + SM_WO + s * 16 * ROW_PITCH + rowoff + j * 32);
#pragma unroll
                for (int j = 0; j < 4; j++) mma16816(y[j], a[j].x, a[j].y, a[j].z, a[j].w, bf[2 * s], bf[2 * s + 1]);
            }
            st_w1(c1_dst, tagw(sel4(y[0][0], y[1][0], y[2][0], y[3][0], t), tag));
            st_w1(c1_dst + NCTA * 8, tagw(sel4(y[0][2], y[1][2], y[2][2], y[3][2], t), tag));
            if (ct == 0) TL(6);
        }
        if (b >= NFFN) return;

        {
            uint4 a[4];
            mbar_wait(bars + (BAR_W1 + (cw >> 1)) * 8);
            {
                const uint32_t ab = sb + SM_W1 + (64 * cw + (mi >> 1) * 8 + ri) * 32 + (((mi & 1) ^ (ri >> 2)) * 16);
#pragma unroll
                for (int s = 0; s < 4; s++) a[s] = ldsm4t(ab + s * 512);
            }
            float* const part_w = reinterpret_cast<float*>(smem + SM_CSP) + (g + 8 * (t & 1)) * 12 + cw;
            const float4* const part_r = reinterpret_cast<const float4*>(smem + SM_CSP + (lane & 15) * 48);
            {
                float cs[4] = {0.f, 0.f, 0.f, 0.f};
#pragma unroll
                for (int s = 0; s < 4; s++) mma16816(cs, a[s].x, a[s].y, a[s].z, a[s].w, 0x3F803F80u, 0x3F803F80u);
                if (t < 2) part_w[0] = selp(cs[2], cs[0], t & 1);
            }
            if (ct == 0) TL(7);
            bar_sync(NB_C2, 352);
            spin_cycles(pc.dlyH);
            uint2 hv = ld_w2(h_src);
            float cs0, cs1, cs2, cs3;
            {
                const float4 u0 = part_r[0], u1 = part_r[1];
                const float2 u2 = *reinterpret_cast<const float2*>(part_r + 2);
                const float cs = ((u0.x + u0.y) + (u0.z + u0.w)) + ((u1.x + u1.y) + (u1.z + u1.w)) + (u2.x + u2.y);
                cs0 = __shfl_sync(FULL, cs, 2 * t); cs1 = __shfl_sync(FULL, cs, 2 * t + 1);
                cs2 = __shfl_sync(FULL, cs, 2 * t + 8); cs3 = __shfl_sync(FULL, cs, 2 * t + 9);
            }
#pragma unroll 1
            for (int n = 0; n < SPIN_LIMIT; n++) {
                if (!__any_sync(FULL, bad2(hv, tag))) break;
                hv = ld_w2(h_src);
            }
            const unsigned hpair = __byte_perm(hv.x, hv.y, 0x7632);
            if (ct == 0) TL(8);
            unsigned hf[8];
#pragma unroll
            for (int s = 0; s < 8; s++) hf[s] = __shfl_sync(FULL, hpair, 4 * s + t);
            float dA[4] = {0.f, 0.f, 0.f, 0.f}, dB[4] = {0.f, 0.f, 0.f, 0.f}, sA[4] = {0.f, 0.f, 0.f, 0.f}, sB[4] = {0.f, 0.f, 0.f, 0.f};
#pragma unroll
            for (int s = 0; s < 4; s += 2) {
                mma16816(dA, a[s].x, a[s].y, a[s].z, a[s].w, hf[2 * s], hf[2 * s + 1]);
                mma16816(dB, a[s + 1].x, a[s + 1].y, a[s + 1].z, a[s + 1].w, hf[2 * s + 2], hf[2 * s + 3]);
                mma16816(sA, hf[2 * s], 0x3F803F80u, hf[2 * s + 1], 0x3F803F80u, hf[2 * s], hf[2 * s + 1]);
                mma16816(sB, hf[2 * s + 2], 0x3F803F80u, hf[2 * s + 3], 0x3F803F80u, hf[2 * s + 2], hf[2 * s + 3]);
            }
            if (t < 2) part_w[192] = selp(dA[2] + dB[2], dA[0] + dB[0], t & 1);
            if (lane == 0) reinterpret_cast<float2*>(smem + SM_FSTAT)[cw] = make_float2(sA[0] + sB[0], sA[2] + sB[2]);
            mbar_wait(bars + BAR_W2 * 8);
            uint4 w[4];
#pragma unroll
            for (int j = 0; j < 4; j++) w[j] = ldsm4t(sb + SM_W2 + rowoff + j * 32);
            bar_sync(NB_FPART, 320);
            const float4 u0 = part_r[48], u1 = part_r[49];
            const float2 u2 = *reinterpret_cast<const float2*>(part_r + 50);
            const float4* fs = reinterpret_cast<const float4*>(smem + SM_FSTAT);
            const float4 q0 = fs[0], q1 = fs[1], q2 = fs[2], q3 = fs[3], q4 = fs[4];
            if (ct == 0) TLD(21, u0.x);
            const float dot = ((u0.x + u0.y) + (u0.z + u0.w)) + ((u1.x + u1.y) + (u1.z + u1.w)) + (u2.x + u2.y);
            const float d0 = __shfl_sync(FULL, dot, 2 * t), d1 = __shfl_sync(FULL, dot, 2 * t + 1);
            const float d2 = __shfl_sync(FULL, dot, 2 * t + 8), d3 = __shfl_sync(FULL, dot, 2 * t + 9);
            const float sq = ((q0.x + q0.z) + (q1.x + q1.z)) + ((q2.x + q2.z) + (q3.x + q3.z)) + (q4.x + q4.z);
            const float sm = ((q0.y + q0.w) + (q1.y + q1.w)) + ((q2.y + q2.w) + (q3.y + q3.w)) + (q4.y + q4.w);
            const float mean = sm * (1.0f / 640.0f);
            const float m2 = bfr(mean);
            const unsigned b0 = pack_bf(fmaxf(fmaf(-m2, cs0, d0), 0.f), fmaxf(fmaf(-m2, cs1, d1), 0.f));
            const unsigned b1 = pack_bf(fmaxf(fmaf(-m2, cs2, d2), 0.f), fmaxf(fmaf(-m2, cs3, d3), 0.f));
            float y[4][4];
#pragma unroll
            for (int j = 0; j < 4; j++) {
                y[j][0] = y[j][1] = y[j][2] = y[j][3] = 0.f;
                mma16816(y[j], w[j].x, w[j].y, w[j].z, w[j].w, b0, b1);
            }
            const float var = fmaxf(fmaf(-mean, mean, sq * (1.0f / 640.0f)), 0.f);
            const float rinv = fast_rcp(bfr(fast_sqrt(bfr(bfr(var) + 1e-5f))));
            st_w1(d_dst, tagw(rinv * sel4(y[0][0], y[1][0], y[2][0], y[3][0], t), tag));
            st_w1(d_dst + NCTA * 8, tagw(rinv * sel4(y[0][2], y[1][2], y[2][2], y[3][2], t), tag));
            if (ct == 0) TL(9);
        }
        bar_arrive(NB_DSENT, 352);
    } else if (warp == 1) {
        const unsigned t0 = gtime32() + (unsigned)((h & 7) * pc.stag);
        if (lane == 0) {
            TL(0);
#pragma unroll
            for (int i = 0; i < NBAR; i++) mbar_init(bars + i * 8, 1);
            asm volatile("fence.mbarrier_init.release.cluster;" ::: "memory");
            asm volatile("prefetch.tensormap [%0];" :: "l"(&map_v) : "memory");
            asm volatile("prefetch.tensormap [%0];" :: "l"(&map_w1) : "memory");
        }
        bar_arrive(NB_XN, NTHREADS);
        if (lane == 0) {
            int tt = pc.tK;
            const char* ks = reinterpret_cast<const char*>(kc) + (size_t)h * 1048576 + 786432 + c * 65536;
#pragma unroll 1
            for (int i = 0; i < 16; i++) {
                wait_until(t0, tt); tt += pc.dKV;
                mbar_expect_tx(bars + (BAR_K + i) * 8, 4096);
                bulk_g2s(sb + SM_K + i * 4096, ks + i * 4096, 4096, bars + (BAR_K + i) * 8);
            }
#pragma unroll 1
            for (int i = 0; i < 16; i++) {
                wait_until(t0, tt); tt += pc.dKV;
                mbar_expect_tx(bars + (BAR_V + i) * 8, 4096);
                tma2d(sb + SM_V + i * 4096, &map_v, 32 * c, h * 4096 + 3072 + 64 * i, bars + (BAR_V + i) * 8);
            }
#pragma unroll 1
            for (int ph = 0; ph < 2; ph++) {
                if (ph == pc.order) {
                    const char* ws = reinterpret_cast<const char*>(wo) + (size_t)b * 32 * 1280;
                    mbar_expect_tx(bars + BAR_WO * 8, 16 * 1280);
                    mbar_expect_tx(bars + (BAR_WO + 1) * 8, 16 * 1280);
#pragma unroll 1
                    for (int j = 0; j < 8; j++) {
                        wait_until(t0, tt); tt += pc.dWO;
#pragma unroll
                        for (int i = 0; i < 4; i++) {
                            const int r = j * 4 + i;
                            bulk_g2s(sb + SM_WO + r * ROW_PITCH, ws + r * 1280, 1280, bars + (BAR_WO + (j >> 2)) * 8);
                        }
                    }
                    tt += pc.gap;
                } else {
#pragma unroll 1
                    for (int j = 0; j < 5; j++) {
                        if (b < NFFN) {
                            wait_until(t0, tt);
                            mbar_expect_tx(bars + (BAR_W1 + j) * 8, 4096);
                            tma2d(sb + SM_W1 + j * 4096, &map_w1, 16 * b, 128 * j, bars + (BAR_W1 + j) * 8);
                        }
                        tt += pc.dW1;
                    }
                }
            }
            if (b < NFFN) {
                const char* w2s = reinterpret_cast<const char*>(w2) + (size_t)b * 16 * 1280;
                mbar_expect_tx(bars + BAR_W2 * 8, 16 * 1280);
#pragma unroll 1
                for (int j = 0; j < 4; j++) {
                    wait_until(t0, tt); tt += pc.dW2;
#pragma unroll
                    for (int i = 0; i < 4; i++) {
                        const int r = j * 4 + i;
                        bulk_g2s(sb + SM_W2 + r * ROW_PITCH, w2s + r * 1280, 1280, bars + BAR_W2 * 8);
                    }
                }
                TL(10);
            }
            if (pc.mode == 1) {
                const int nb = (b < NFFN) ? NBAR : BAR_W1;
                for (int i = 0; i < nb; i++) mbar_wait(bars + i * 8);
            }
        }
    } else {
        const unsigned t0 = gtime32();
        uint2 xr[5];
#pragma unroll
        for (int j = 0; j < 5; j++) xr[j] = ldg_nc8(reinterpret_cast<const uint2*>(x) + j * 32 + lane);
        unsigned epoch;
        asm volatile("ld.relaxed.gpu.global.u32 %0, [%1];" : "=r"(epoch) : "l"(&g_epoch) : "memory");
        const int col = 8 * b + 4 * (lane & 1) + (lane & 2) + ((lane >> 2) & 1);
        float xcol = 0.f;
        if (b < NOCT) xcol = __bfloat162float(x[col]);
        {
            float s = 0.f;
#pragma unroll
            for (int j = 0; j < 5; j++) s += (bf_lo(xr[j].x) + bf_hi(xr[j].x)) + (bf_lo(xr[j].y) + bf_hi(xr[j].y));
#pragma unroll
            for (int o = 16; o; o >>= 1) s += __shfl_xor_sync(FULL, s, o);
            const float mean = s * (1.0f / 640.0f);
            float v = 0.f;
#pragma unroll
            for (int j = 0; j < 5; j++) {
                float d0 = bf_lo(xr[j].x) - mean, d1 = bf_hi(xr[j].x) - mean, d2 = bf_lo(xr[j].y) - mean, d3 = bf_hi(xr[j].y) - mean;
                v += (d0 * d0 + d1 * d1) + (d2 * d2 + d3 * d3);
            }
#pragma unroll
            for (int o = 16; o; o >>= 1) v += __shfl_xor_sync(FULL, v, o);
            const float mb = bfr(mean);
            const float rb = __frcp_rn(bfr(__fsqrt_rn(bfr(bfr(v * (1.0f / 640.0f)) + 1e-5f))));
            float4* xn = reinterpret_cast<float4*>(smem + SM_XN);
#pragma unroll
            for (int j = 0; j < 5; j++) {
                float4 o;
                o.x = bfr(bfr(bf_lo(xr[j].x) - mb) * rb); o.y = bfr(bfr(bf_hi(xr[j].x) - mb) * rb);
                o.z = bfr(bfr(bf_lo(xr[j].y) - mb) * rb); o.w = bfr(bfr(bf_hi(xr[j].y) - mb) * rb);
                xn[j * 32 + lane] = o;
            }
        }
        const unsigned tag = 1u + (epoch & 1u);
        if (lane == 0) *reinterpret_cast<volatile unsigned*>(smem + SM_TAG) = tag;
        if (lane == 0) TL(22);
        bar_sync(NB_XN, NTHREADS);
        {
            const unsigned e = 0u;
            if (pc.prew & 8) st_w4(&g_xa[b * 128 + 4 * lane], make_uint4(e, e, e, e));
            if ((pc.prew & 16) && b < NOCT) st_w1(&g_xc2[(lane >> 3) * 640 + col], e);
        }
        bar_sync(NB_QPART, 352);
        {
            const float4* qp = reinterpret_cast<const float4*>(smem + SM_QPART) + lane;
            float4 s = qp[0];
            if (lane == 0) TLD(1, s.x);
#pragma unroll
            for (int w = 1; w < 10; w++) { const float4 u = qp[w * 32]; s.x += u.x; s.y += u.y; s.z += u.z; s.w += u.w; }
            const uint4 mine = make_uint4(tagw(s.x, tag), tagw(s.y, tag), tagw(s.z, tag), tagw(s.w, tag));
            st_w4(&g_xa[b * 128 + 4 * lane], mine);
            if (pc.mode == 1) return;
            const unsigned* pa = &g_xa[h * 512 + 4 * lane];
            __nanosleep(300);
            uint4 v[4];
#pragma unroll 1
            for (int n = 0; n < SPIN_LIMIT; n++) {
#pragma unroll
                for (int cc = 0; cc < 4; cc++) v[cc] = (cc == c) ? mine : ld_w4(pa + cc * 128);
                if (!__any_sync(FULL, bad4(v[0], tag) | bad4(v[1], tag) | bad4(v[2], tag) | bad4(v[3], tag))) break;
                __nanosleep(100);
            }
            const float q0 = ((untag(v[0].x) + untag(v[1].x)) + untag(v[2].x)) + untag(v[3].x);
            const float q1 = ((untag(v[0].y) + untag(v[1].y)) + untag(v[2].y)) + untag(v[3].y);
            const float q2 = ((untag(v[0].z) + untag(v[1].z)) + untag(v[2].z)) + untag(v[3].z);
            const float q3 = ((untag(v[0].w) + untag(v[1].w)) + untag(v[2].w)) + untag(v[3].w);
            reinterpret_cast<uint2*>(smem + SM_QS)[lane] = make_uint2(pack_bf(q0, q1), pack_bf(q2, q3));
        }
        bar_arrive(NB_Q, 288);
        if (lane == 0) TL(2);
        if (b >= NFFN) return;
        const unsigned* const c1_src = pin(&g_xc1[((b < NOCT) ? b : b - NOCT) * (NCTA * 8) + 4 * lane]);
        const unsigned* const d_src = pin(&g_xd[b * (NCTA * 8) + 4 * lane]);
        unsigned* const h_dst = pin(&g_xc2[(lane >> 3) * 640 + col]);
        __nv_bfloat16* const o_dst = pin(out + col);
        int lane_p = lane, dly_d = pc.dlyD;
        asm volatile("" : "+r"(lane_p), "+r"(dly_d));
        float hcol = 0.f;
        {
            wait_until(t0, pc.tC);
            const float sum = reduce_inbox<NCTA>(c1_src, tag, lane_p);
            hcol = bfr(xcol + bfr(sum));
            if (b < NOCT) st_w1(h_dst, __float_as_uint(hcol) | tag);
            if (lane == 0) TL(12);
        }
        bar_arrive(NB_C2, 352);
        bar_sync(NB_DSENT, 352);
        if (b >= NOCT) return;
        spin_cycles(dly_d);
        {
            const float y = reduce_inbox<NFFN>(d_src, tag, lane_p);
            if (lane_p < 8) asm volatile("st.global.u16 [%0], %1;" :: "l"(o_dst), "h"((unsigned short)pack_bf(hcol + bfr(y), 0.f)) : "memory");
            if (lane == 0) TL(13);
            if (b == 0 && lane == 0) st_w1(&g_epoch, epoch + 1u);
        }
    }
}

Pace g_pace = {1250, 165, 206, 139, 174, 20, 200, 31, 0, 100, 9700, 0, 300, 6};
int g_w1_promo = 2;
int g_v_promo = 2;

}

typedef CUresult (*EncodeTiledFn)(CUtensorMap*, CUtensorMapDataType, cuuint32_t, void*, const cuuint64_t*, const cuuint64_t*,
                                  const cuuint32_t*, const cuuint32_t*, CUtensorMapInterleave, CUtensorMapSwizzle,
                                  CUtensorMapL2promotion, CUtensorMapFloatOOBfill);

extern "C" void kernel_launch(void* const* d_in, const int* in_sizes, int n_in, void* d_out, int out_size) {
    (void)in_sizes; (void)n_in; (void)out_size;
    static EncodeTiledFn encode = nullptr;
    if (!encode) {
        cudaFuncSetAttribute(fk::fused_decode_kernel, cudaFuncAttributeMaxDynamicSharedMemorySize, fk::SMEM_BYTES);
        void* fn = nullptr;
        cudaDriverEntryPointQueryResult qres;
        cudaGetDriverEntryPoint("cuTensorMapEncodeTiled", &fn, cudaEnableDefault, &qres);
        encode = (EncodeTiledFn)fn;
    }
    CUtensorMap map_v, map_w1;
    {
        const cuuint64_t dims[2] = {128, 32 * 4096}, strides[1] = {256};
        const cuuint32_t box[2] = {32, 64}, es[2] = {1, 1};
        encode(&map_v, CU_TENSOR_MAP_DATA_TYPE_BFLOAT16, 2, d_in[2], dims, strides, box, es, CU_TENSOR_MAP_INTERLEAVE_NONE,
               CU_TENSOR_MAP_SWIZZLE_64B, (CUtensorMapL2promotion)fk::g_v_promo, CU_TENSOR_MAP_FLOAT_OOB_FILL_NONE);
    }
    {
        const cuuint64_t dims[2] = {1728, 640}, strides[1] = {3456};
        const cuuint32_t box[2] = {16, 128}, es[2] = {1, 1};
        encode(&map_w1, CU_TENSOR_MAP_DATA_TYPE_BFLOAT16, 2, d_in[6], dims, strides, box, es, CU_TENSOR_MAP_INTERLEAVE_NONE,
               CU_TENSOR_MAP_SWIZZLE_32B, (CUtensorMapL2promotion)fk::g_w1_promo, CU_TENSOR_MAP_FLOAT_OOB_FILL_NONE);
    }
    fk::fused_decode_kernel<<<fk::NCTA, fk::NTHREADS, fk::SMEM_BYTES>>>(
        (const __nv_bfloat16*)d_in[0], (const __nv_bfloat16*)d_in[1], (const __nv_bfloat16*)d_in[3],
        (const __nv_bfloat16*)d_in[4], (const __nv_bfloat16*)d_in[7], (__nv_bfloat16*)d_out, fk::g_pace, map_v, map_w1);
}
```

```cpp
#include <cuda_runtime.h>
#include <cuda.h>
#include <cuda_bf16.h>
#include <stdint.h>
#include <stdlib.h>

namespace fk {

constexpr int NCTA = 128;
constexpr int NFFN = 108;
constexpr int NOCT = 80;
constexpr int NTHREADS = 384;

constexpr int ROW_PITCH = 1296;
constexpr int SM_K = 0;
constexpr int SM_V = 65536;
constexpr int SM_W1 = 131072;
constexpr int SM_WO = SM_W1 + 640 * 32;
constexpr int SM_W2 = SM_WO + 32 * ROW_PITCH;
constexpr int SM_QPART = SM_W2 + 16 * ROW_PITCH;
constexpr int SM_P = SM_QPART + 4096;
constexpr int SM_XN = SM_P + 2048;
constexpr int SM_OPART = SM_XN + 2560;
constexpr int SM_ML = SM_OPART + 1024;
constexpr int SM_QS = SM_ML + 64;
constexpr int SM_CSP = SM_QS + 256;
constexpr int SM_DP = SM_CSP + 768;
constexpr int SM_TAG = SM_DP + 896;
constexpr int SM_BAR = SM_TAG + 32;
constexpr int BAR_K = 0, BAR_V = 16, BAR_WO = 32, BAR_W1 = 34, BAR_W2 = 39, BAR_SIG = 40, BAR_SIDE = 41, BAR_CLR = 42, NBAR = 43;
constexpr int SMEM_BYTES = SM_BAR + NBAR * 8;

constexpr int SPIN_LIMIT = 1 << 20;

struct Pace {
    int tK;
    int dKV;
    int dWO;
    int dW1;
    int dW2;
    int stag;
    int gap;
    int dlyD;
    int sV;
    int nprobe;
    int tP;
    int dry;
    int mode;
    int rotK;
    int rotV;
};

__device__ __align__(4096) unsigned g_scr[1 << 20];
constexpr int PAIR_W = 2048, REP_W = 1024;
constexpr int PR_C1 = 0;
constexpr int PR_D = 80;
constexpr int PR_H = 160;
constexpr int PR_S = 162;
constexpr int PR_A = 194;
constexpr int PR_SIDE = 202;
constexpr int PR_PROBE = 203;
constexpr int PR_EPOCH = 235;
constexpr int PR_TL = 236;
__device__ __forceinline__ int near_off(int pair, unsigned side) {
    return pair * PAIR_W + (int)((side ^ __popc((2 * pair) & 0xb3)) & 1u) * REP_W;
}
#define TL(i) do {} while (0)
#define TLD(i, v) do {} while (0)
#define TLV(i, v) do {} while (0)

__device__ __forceinline__ unsigned gtime32() {
    unsigned long long t; asm volatile("mov.u64 %0, %globaltimer;" : "=l"(t) :: "memory"); return (unsigned)t;
}
__device__ __forceinline__ uint32_t smem_u32(const void* p) { return (uint32_t)__cvta_generic_to_shared(p); }
__device__ __forceinline__ void mbar_init(uint32_t bar, uint32_t cnt) {
    asm volatile("mbarrier.init.shared::cta.b64 [%0], %1;" :: "r"(bar), "r"(cnt) : "memory");
}
__device__ __forceinline__ void mbar_expect_tx(uint32_t bar, uint32_t bytes) {
    asm volatile("mbarrier.arrive.expect_tx.shared::cta.b64 _, [%0], %1;" :: "r"(bar), "r"(bytes) : "memory");
}
__device__ __forceinline__ void mbar_arrive(uint32_t bar) {
    asm volatile("mbarrier.arrive.shared::cta.b64 _, [%0];" :: "r"(bar) : "memory");
}
__device__ __forceinline__ void mbar_arrive_p(uint32_t bar, unsigned p) {
    asm volatile("{\n.reg .pred p;\nsetp.ne.u32 p, %1, 0;\n@p mbarrier.arrive.shared::cta.b64 _, [%0];\n}" :: "r"(bar), "r"(p) : "memory");
}
__device__ __forceinline__ bool mbar_test(uint32_t bar) {
    uint32_t ok;
    asm volatile("{\n.reg .pred p;\nmbarrier.test_wait.parity.shared::cta.b64 p, [%1], 0;\nselp.u32 %0, 1, 0, p;\n}"
                 : "=r"(ok) : "r"(bar) : "memory");
    return ok != 0;
}
__device__ __forceinline__ bool mbar_try(uint32_t bar) {
    uint32_t ok;
    asm volatile("{\n.reg .pred p;\nmbarrier.try_wait.parity.shared::cta.b64 p, [%1], 0;\nselp.u32 %0, 1, 0, p;\n}"
                 : "=r"(ok) : "r"(bar) : "memory");
    return ok != 0;
}
__device__ __forceinline__ void mbar_wait(uint32_t bar, int lim = SPIN_LIMIT) {
#pragma unroll 1
    for (int n = 0; n < lim; n++) if (mbar_try(bar)) break;
}
__device__ __forceinline__ void bulk_g2s(uint32_t dst, const void* src, uint32_t bytes, uint32_t bar) {
    asm volatile("cp.async.bulk.shared::cluster.global.mbarrier::complete_tx::bytes [%0], [%1], %2, [%3];"
                 :: "r"(dst), "l"(src), "r"(bytes), "r"(bar) : "memory");
}
__device__ __forceinline__ void tma2d(uint32_t dst, const CUtensorMap* map, int c0, int c1, uint32_t bar) {
    asm volatile("cp.async.bulk.tensor.2d.shared::cluster.global.mbarrier::complete_tx::bytes [%0], [%1, {%3, %4}], [%2];"
                 :: "r"(dst), "l"(map), "r"(bar), "r"(c0), "r"(c1) : "memory");
}
__device__ __forceinline__ unsigned tagw(float v, unsigned tag) { return (__float_as_uint(v) & ~3u) | tag; }
__device__ __forceinline__ float untag(unsigned w) { return __uint_as_float(w & ~3u); }
__device__ __forceinline__ void st_w1(unsigned* p, unsigned a) {
    asm volatile("st.relaxed.gpu.global.u32 [%0], %1;" :: "l"(p), "r"(a) : "memory");
}
__device__ __forceinline__ void st_w1_p(unsigned* a, unsigned v, unsigned p) {
    asm volatile("{\n.reg .pred p;\nsetp.ne.u32 p, %2, 0;\n@p st.relaxed.gpu.global.u32 [%0], %1;\n}" :: "l"(a), "r"(v), "r"(p) : "memory");
}
__device__ __forceinline__ void st_w4(unsigned* p, uint4 v) {
    asm volatile("st.relaxed.gpu.global.v4.u32 [%0], {%1,%2,%3,%4};" :: "l"(p), "r"(v.x), "r"(v.y), "r"(v.z), "r"(v.w) : "memory");
}
__device__ __forceinline__ unsigned ld_w1(const unsigned* p) {
    unsigned v;
    asm volatile("ld.relaxed.gpu.global.u32 %0, [%1];" : "=r"(v) : "l"(p) : "memory");
    return v;
}
__device__ __forceinline__ uint4 ld_w4(const unsigned* p) {
    uint4 v;
    asm volatile("ld.relaxed.gpu.global.v4.u32 {%0,%1,%2,%3}, [%4];" : "=r"(v.x), "=r"(v.y), "=r"(v.z), "=r"(v.w) : "l"(p) : "memory");
    return v;
}
__device__ __forceinline__ uint2 ld_w2(const unsigned* p) {
    uint2 v;
    asm volatile("ld.relaxed.gpu.global.v2.u32 {%0,%1}, [%2];" : "=r"(v.x), "=r"(v.y) : "l"(p) : "memory");
    return v;
}
__device__ __forceinline__ bool bad2(uint2 v, unsigned tag) { return (v.x & v.y & tag) == 0; }
__device__ __forceinline__ bool bad4(uint4 v, unsigned tag) { return ((v.x & v.y & v.z) & v.w & tag) == 0; }

__device__ __forceinline__ void bar_sync(int id, int n) { __syncwarp(); asm volatile("bar.sync %0, %1;" :: "r"(id), "r"(n) : "memory"); }
__device__ __forceinline__ void bar_arrive(int id, int n) { __syncwarp(); asm volatile("bar.arrive %0, %1;" :: "r"(id), "r"(n) : "memory"); }
template <int ID, int N> __device__ __forceinline__ void bar_sync_p(unsigned p) {
    __syncwarp();
    asm volatile("{\n.reg .pred p;\nsetp.ne.u32 p, %0, 0;\n@p bar.sync %1, %2;\n}" :: "r"(p), "n"(ID), "n"(N) : "memory");
}
template <int ID, int N> __device__ __forceinline__ void bar_arrive_p(unsigned p) {
    __syncwarp();
    asm volatile("{\n.reg .pred p;\nsetp.ne.u32 p, %0, 0;\n@p bar.arrive %1, %2;\n}" :: "r"(p), "n"(ID), "n"(N) : "memory");
}
__device__ __forceinline__ void sts_p(uint32_t a, float v, unsigned p) {
    asm volatile("{\n.reg .pred p;\nsetp.ne.u32 p, %2, 0;\n@p st.shared.f32 [%0], %1;\n}" :: "r"(a), "f"(v), "r"(p) : "memory");
}
__device__ __forceinline__ float bf_lo(unsigned u) { return __uint_as_float(u << 16); }
__device__ __forceinline__ float bf_hi(unsigned u) { return __uint_as_float(u & 0xffff0000u); }
__device__ __forceinline__ unsigned pack_bf(float lo, float hi) {
    unsigned r; asm("cvt.rn.bf16x2.f32 %0, %1, %2;" : "=r"(r) : "f"(hi), "f"(lo)); return r;
}
__device__ __forceinline__ float bfr(float v) { return __uint_as_float(pack_bf(0.f, v)); }
__device__ __forceinline__ float selp(float a, float b, unsigned c) {
    float r; asm("{\n.reg .pred p;\nsetp.ne.u32 p, %3, 0;\nselp.f32 %0, %1, %2, p;\n}" : "=f"(r) : "f"(a), "f"(b), "r"(c)); return r;
}
__device__ __forceinline__ float sel4(float a0, float a1, float a2, float a3, int t) {
    return selp(selp(a3, a2, t & 1), selp(a1, a0, t & 1), t & 2);
}
__device__ __forceinline__ float fast_sqrt(float v) { float r; asm("sqrt.approx.ftz.f32 %0, %1;" : "=f"(r) : "f"(v)); return r; }
__device__ __forceinline__ float fast_rcp(float v) { float r; asm("rcp.approx.ftz.f32 %0, %1;" : "=f"(r) : "f"(v)); return r; }
template <class T> __device__ __forceinline__ T* pin(T* p) { asm volatile("" : "+l"(p)); return p; }
__device__ __forceinline__ void mma16816(float (&c)[4], unsigned a0, unsigned a1, unsigned a2, unsigned a3,
                                         unsigned b0, unsigned b1) {
    asm volatile("mma.sync.aligned.m16n8k16.row.col.f32.bf16.bf16.f32 {%0,%1,%2,%3}, {%4,%5,%6,%7}, {%8,%9}, {%0,%1,%2,%3};"
                 : "+f"(c[0]), "+f"(c[1]), "+f"(c[2]), "+f"(c[3])
                 : "r"(a0), "r"(a1), "r"(a2), "r"(a3), "r"(b0), "r"(b1));
}
__device__ __forceinline__ uint4 ldsm4t(uint32_t addr) {
    uint4 r;
    asm volatile("ldmatrix.sync.aligned.m8n8.x4.trans.shared.b16 {%0,%1,%2,%3}, [%4];"
                 : "=r"(r.x), "=r"(r.y), "=r"(r.z), "=r"(r.w) : "r"(addr) : "memory");
    return r;
}
__device__ __forceinline__ uint4 lds16(uint32_t addr) {
    uint4 r;
    asm volatile("ld.shared.v4.u32 {%0,%1,%2,%3}, [%4];" : "=r"(r.x), "=r"(r.y), "=r"(r.z), "=r"(r.w) : "r"(addr) : "memory");
    return r;
}
__device__ __forceinline__ void wait_until(unsigned t0, int t) {
#pragma unroll 1
    for (int n = 0; n < SPIN_LIMIT; n++) if ((int)(gtime32() - t0) >= t) break;
}
__device__ __forceinline__ void spin_cycles(int n) {
    if (n > 0) { const unsigned c0 = clock(); while ((int)(clock() - c0) < n) {} }
}
__device__ __forceinline__ float octet_reduce(float v0, float v1, float v2, float v3, int lane) {
    const unsigned FULL = 0xffffffffu;
    const unsigned b1 = lane & 2, b2 = lane & 4;
    float k0 = selp(v2, v0, b1), k1 = selp(v3, v1, b1);
    const float s0 = selp(v0, v2, b1), s1 = selp(v1, v3, b1);
    k0 += __shfl_xor_sync(FULL, s0, 2);
    k1 += __shfl_xor_sync(FULL, s1, 2);
    float k = selp(k1, k0, b2);
    const float s = selp(k0, k1, b2);
    k += __shfl_xor_sync(FULL, s, 4);
    k += __shfl_xor_sync(FULL, k, 8);
    k += __shfl_xor_sync(FULL, k, 16);
    return k;
}

constexpr int NB_XN = 1, NB_QPART = 2, NB_Q = 3, NB_OPART = 4, NB_FPART = 5, NB_DSENT = 6, NB_CS = 7, NB_PROBE = 8, NB_TAG0 = 9, NB_TAG1 = 10;
constexpr int N_XN = NTHREADS - 64;

__global__ void __launch_bounds__(NTHREADS, 1)
fused_decode_kernel(const __nv_bfloat16* __restrict__ x, const __nv_bfloat16* __restrict__ wq,
                    const __nv_bfloat16* __restrict__ kc, const __nv_bfloat16* __restrict__ wo,
                    const __nv_bfloat16* __restrict__ w2, __nv_bfloat16* __restrict__ out, unsigned* __restrict__ scr, const Pace pc,
                    const __grid_constant__ CUtensorMap map_v, const __grid_constant__ CUtensorMap map_w1) {
    extern __shared__ __align__(1024) unsigned char smem[];
    const unsigned tstart = gtime32();
    const int tid = threadIdx.x, warp = tid >> 5, lane = tid & 31;
    const int b = blockIdx.x, h = b >> 2, c = b & 3;
    const int cw = warp - 2, ct = tid - 64;

    uint2 xr[5];
    unsigned epoch;
    uint4 wr[10];
    {
        const char* wp = reinterpret_cast<const char*>(wq) + (size_t)(160 * c + (ct >> 4)) * 8192 + h * 256 + (ct & 15) * 16;
        const uint2* xp = reinterpret_cast<const uint2*>(x) + lane;
        asm volatile("{\n.reg .pred p;\nsetp.ne.u32 p, %13, 0;\n@p bra.uni XSKIP;\n"
                     "ld.global.nc.v2.u32 {%0,%1}, [%11];\nld.global.nc.v2.u32 {%2,%3}, [%11+256];\nld.global.nc.v2.u32 {%4,%5}, [%11+512];\n"
                     "ld.global.nc.v2.u32 {%6,%7}, [%11+768];\nld.global.nc.v2.u32 {%8,%9}, [%11+1024];\n"
                     "ld.relaxed.gpu.global.u32 %10, [%12];\nXSKIP:\n}"
                     : "=r"(xr[0].x), "=r"(xr[0].y), "=r"(xr[1].x), "=r"(xr[1].y), "=r"(xr[2].x), "=r"(xr[2].y), "=r"(xr[3].x), "=r"(xr[3].y),
                       "=r"(xr[4].x), "=r"(xr[4].y), "=r"(epoch)
                     : "l"(xp), "l"(scr + PR_EPOCH * PAIR_W), "r"(warp) : "memory");
        asm volatile("{\n.reg .pred p;\nsetp.ge.u32 p, %41, 8;\n@p bra.uni WSKIP;\n"
                     "ld.global.nc.L1::no_allocate.v4.u32 {%0,%1,%2,%3}, [%40];\n"
                     "ld.global.nc.L1::no_allocate.v4.u32 {%4,%5,%6,%7}, [%40+131072];\n"
                     "ld.global.nc.L1::no_allocate.v4.u32 {%8,%9,%10,%11}, [%40+262144];\n"
                     "ld.global.nc.L1::no_allocate.v4.u32 {%12,%13,%14,%15}, [%40+393216];\n"
                     "ld.global.nc.L1::no_allocate.v4.u32 {%16,%17,%18,%19}, [%40+524288];\n"
                     "ld.global.nc.L1::no_allocate.v4.u32 {%20,%21,%22,%23}, [%40+655360];\n"
                     "ld.global.nc.L1::no_allocate.v4.u32 {%24,%25,%26,%27}, [%40+786432];\n"
                     "ld.global.nc.L1::no_allocate.v4.u32 {%28,%29,%30,%31}, [%40+917504];\n"
                     "ld.global.nc.L1::no_allocate.v4.u32 {%32,%33,%34,%35}, [%40+1048576];\n"
                     "ld.global.nc.L1::no_allocate.v4.u32 {%36,%37,%38,%39}, [%40+1179648];\n"
                     "WSKIP:\n}"
                     : "=r"(wr[0].x), "=r"(wr[0].y), "=r"(wr[0].z), "=r"(wr[0].w), "=r"(wr[1].x), "=r"(wr[1].y), "=r"(wr[1].z), "=r"(wr[1].w),
                       "=r"(wr[2].x), "=r"(wr[2].y), "=r"(wr[2].z), "=r"(wr[2].w), "=r"(wr[3].x), "=r"(wr[3].y), "=r"(wr[3].z), "=r"(wr[3].w),
                       "=r"(wr[4].x), "=r"(wr[4].y), "=r"(wr[4].z), "=r"(wr[4].w), "=r"(wr[5].x), "=r"(wr[5].y), "=r"(wr[5].z), "=r"(wr[5].w),
                       "=r"(wr[6].x), "=r"(wr[6].y), "=r"(wr[6].z), "=r"(wr[6].w), "=r"(wr[7].x), "=r"(wr[7].y), "=r"(wr[7].z), "=r"(wr[7].w),
                       "=r"(wr[8].x), "=r"(wr[8].y), "=r"(wr[8].z), "=r"(wr[8].w), "=r"(wr[9].x), "=r"(wr[9].y), "=r"(wr[9].z), "=r"(wr[9].w)
                     : "l"(wp), "r"(cw));
    }
    if (ct == 0) TL(15);

    const uint32_t sb = smem_u32(smem);
    const uint32_t bars = sb + SM_BAR;
    const int g = lane >> 2, t = lane & 3;
    const unsigned FULL = 0xffffffffu;
    volatile unsigned* const misc = reinterpret_cast<volatile unsigned*>(smem + SM_TAG);

    if ((unsigned)cw < 10u) {
        const int mi = lane >> 3, ri = lane & 7;
        unsigned tag;
        unsigned real = 1;
        if (cw < 8) {
            bar_sync(NB_XN, N_XN);
            tag = misc[0];
            unsigned* const s_dst = scr + (PR_S + h) * PAIR_W + c * 256 + (cw + 8 * (t >> 1)) * 16 + 8 * (t & 1) + g;
            st_w1(s_dst, 0u); st_w1(s_dst + REP_W, 0u);
            {
                const float* xn = reinterpret_cast<const float*>(smem + SM_XN) + 160 * c + (ct >> 4);
                float acc[8];
#pragma unroll
                for (int j = 0; j < 8; j++) acc[j] = 0.f;
#pragma unroll
                for (int i = 0; i < 10; i++) {
                    const float xv = xn[16 * i];
                    acc[0] = fmaf(xv, bf_lo(wr[i].x), acc[0]); acc[1] = fmaf(xv, bf_hi(wr[i].x), acc[1]);
                    acc[2] = fmaf(xv, bf_lo(wr[i].y), acc[2]); acc[3] = fmaf(xv, bf_hi(wr[i].y), acc[3]);
                    acc[4] = fmaf(xv, bf_lo(wr[i].z), acc[4]); acc[5] = fmaf(xv, bf_hi(wr[i].z), acc[5]);
                    acc[6] = fmaf(xv, bf_lo(wr[i].w), acc[6]); acc[7] = fmaf(xv, bf_hi(wr[i].w), acc[7]);
                }
#pragma unroll
                for (int j = 0; j < 8; j++) acc[j] += __shfl_xor_sync(FULL, acc[j], 16);
                if (lane < 16) {
                    float4* qp = reinterpret_cast<float4*>(smem + SM_QPART + cw * 512 + lane * 32);
                    qp[0] = make_float4(acc[0], acc[1], acc[2], acc[3]);
                    qp[1] = make_float4(acc[4], acc[5], acc[6], acc[7]);
                }
            }
            bar_arrive(NB_QPART, 288);
            if (pc.mode == 1) return;
            bar_sync(NB_Q, 288);
            uint4 qf[4];
#pragma unroll
            for (int j = 0; j < 4; j++) qf[j] = lds16(sb + SM_QS + 16 * (t + 4 * (j ^ (g & 1))));
            float mys = 0.f;
#pragma unroll 1
            for (int tile = 0; tile < 2; tile++) {
                const int ch = cw + 8 * tile;
                mbar_wait(bars + (BAR_K + ch) * 8);
                const uint32_t kb = sb + SM_K + ch * 4096 + g * 256 + t * 16;
                float cA[4] = {0.f, 0.f, 0.f, 0.f}, cB[4] = {0.f, 0.f, 0.f, 0.f};
#pragma unroll
                for (int j = 0; j < 4; j++) {
                    const uint32_t a = kb + 64 * (j ^ (g & 1));
                    const uint4 ra = lds16(a), rb = lds16(a + 2048);
                    mma16816(cA, ra.x, rb.x, ra.y, rb.y, qf[j].x, qf[j].y);
                    mma16816(cB, ra.z, rb.z, ra.w, rb.w, qf[j].z, qf[j].w);
                }
                const float s0 = selp(cA[1] + cB[1], cA[0] + cB[0], g & 1);
                const float s1 = selp(cA[3] + cB[3], cA[2] + cB[2], g & 1);
                mys = selp(selp(s1, s0, t & 1), mys, (t >> 1) == tile);
            }
            mys = bfr(bfr(mys) * 0.08838834764831845f);
            st_w1(s_dst, __float_as_uint(mys) | tag);
            st_w1(s_dst + REP_W, __float_as_uint(mys) | tag);
            if (ct == 224) TL(3);
            {
                mbar_wait(bars + (BAR_V + ((pc.sV + h * pc.rotV) & 15)) * 8);
                mbar_wait(bars + BAR_SIDE * 8);
                const unsigned* ps = scr + near_off(PR_S + h, misc[1]) + (cw + 8 * (lane >> 4)) * 64 + 4 * (lane & 15);
                uint4 v = ld_w4(ps);
#pragma unroll 1
                for (int n = 0; n < SPIN_LIMIT; n++) {
                    if (!__any_sync(FULL, bad4(v, tag))) break;
                    __nanosleep(200);
                    v = ld_w4(ps);
                }
                if (ct == 224) TL(28);
                const float e0 = untag(v.x), e1 = untag(v.y), e2 = untag(v.z), e3 = untag(v.w);
                float m = fmaxf(fmaxf(e0, e1), fmaxf(e2, e3));
#pragma unroll
                for (int o = 16; o; o >>= 1) m = fmaxf(m, __shfl_xor_sync(FULL, m, o));
                const unsigned p01 = pack_bf(__expf(e0 - m), __expf(e1 - m)), p23 = pack_bf(__expf(e2 - m), __expf(e3 - m));
                reinterpret_cast<uint2*>(smem + SM_P)[cw * 32 + lane] = make_uint2(p01, p23);
                float l = (bf_lo(p01) + bf_hi(p01)) + (bf_lo(p23) + bf_hi(p23));
#pragma unroll
                for (int o = 16; o; o >>= 1) l += __shfl_xor_sync(FULL, l, o);
                if (lane == 0) reinterpret_cast<float2*>(smem + SM_ML)[cw] = make_float2(m, l);
                __syncwarp();
                if (ct == 224) TL(5);
            }
            float o0[4] = {0.f, 0.f, 0.f, 0.f}, o1[4] = {0.f, 0.f, 0.f, 0.f};
            const int vrow = (mi >> 1) * 8 + ri;
            const uint32_t va0 = vrow * 64 + (((mi & 1) ^ ((ri >> 1) & 3)) * 16);
            const uint32_t va1 = vrow * 64 + (((2 + (mi & 1)) ^ ((ri >> 1) & 3)) * 16);
#pragma unroll 1
            for (int tile = 0; tile < 2; tile++) {
                const int ch = cw + 8 * tile;
                const unsigned* pp = reinterpret_cast<const unsigned*>(smem + SM_P) + cw * 64 + tile * 32 + t;
                unsigned pf[8];
#pragma unroll
                for (int s = 0; s < 8; s++) pf[s] = pp[4 * s];
                mbar_wait(bars + (BAR_V + ch) * 8);
                const uint32_t vb = sb + SM_V + ch * 4096;
#pragma unroll
                for (int s = 0; s < 4; s++) {
                    const uint4 a0 = ldsm4t(vb + s * 1024 + va0), a1 = ldsm4t(vb + s * 1024 + va1);
                    mma16816(o0, a0.x, a0.y, a0.z, a0.w, pf[2 * s], pf[2 * s + 1]);
                    mma16816(o1, a1.x, a1.y, a1.z, a1.w, pf[2 * s], pf[2 * s + 1]);
                }
            }
            reinterpret_cast<float*>(smem + SM_OPART)[cw * 32 + 8 * t + g] = sel4(o0[0], o0[2], o1[0], o1[2], t);
        } else {
            unsigned* const probe = scr + near_off(PR_PROBE + (b >> 2), cw & 1) + (b & 3) * 256;
            st_w1(probe + (lane >> 3) * 32 + (lane & 7), 0u);
            st_w1(probe + 128 + (lane >> 3) * 32 + (lane & 7), 0u);
            if (cw == 8 && lane == 0) misc[2] = 0u;
            wait_until(tstart, pc.tP);
            bar_sync(NB_PROBE, 64);
            unsigned v = 0;
#pragma unroll 1
            for (int i = 0; i < pc.nprobe; i++) v = ld_w1(probe + i * 32 + v);
            unsigned won = 0;
            if (lane == 0) won = (atomicExch(reinterpret_cast<unsigned*>(smem + SM_TAG) + 2, 1u + v) == 0u);
            won = __shfl_sync(FULL, won, 0);
            if (cw & 1) bar_sync(NB_TAG1, 64); else bar_sync(NB_TAG0, 64);
            tag = misc[0];
            if (pc.mode == 1) return;
            if (won) {
                const unsigned sd = cw & 1;
                if (lane == 0) {
                    misc[1] = sd;
                    mbar_arrive(bars + BAR_SIDE * 8);
                    TL(23);
                }
                if (b < NOCT) {
                    unsigned* i0 = scr + near_off(PR_C1 + b, sd) + 4 * lane;
                    unsigned* i1 = scr + near_off(PR_D + b, sd) + 4 * lane;
#pragma unroll
                    for (int j = 0; j < 8; j++) {
                        const unsigned f = (j * 16 + (lane >> 1) >= NFFN) ? tag : 0u;
                        st_w4(i0 + 128 * j, make_uint4(0u, 0u, 0u, 0u));
                        st_w4(i1 + 128 * j, make_uint4(f, f, f, f));
                    }
                    __threadfence();
                    __syncwarp();
                    if (lane < 16) st_w1(scr + PR_SIDE * PAIR_W + (lane >> 3) * REP_W + b * 8 + (lane & 7), (sd << 2) | tag);
                    if (lane == 0) { mbar_arrive(bars + BAR_CLR * 8); TL(30); }
                }
                real = !(pc.dry & 1);
            }
        }

        const uint32_t rowoff = ((mi >> 1) * 8 + ri) * ROW_PITCH + cw * 128 + (mi & 1) * 16;
        const int oct = 2 * (4 * cw + t);
#pragma unroll 1
        while (true) {
            asm volatile("" : "+r"(real));
            const int lim = real ? SPIN_LIMIT : 0;
            bar_sync_p<NB_OPART, 320>(real);
            mbar_wait(bars + BAR_SIDE * 8, lim);
            const unsigned side = misc[1];
            const unsigned* const sd_src = scr + near_off(PR_SIDE, side) + oct * 8;
            unsigned sd0 = tag, sd1 = tag;
            if (real) { sd0 = ld_w1(sd_src); sd1 = ld_w1(sd_src + 8); }
            const unsigned* const h_src = pin(scr + near_off(PR_H + (b & 1), side) + 2 * ct);

            unsigned *c1_a, *c1_b, *d_a, *d_b;
            {
                const float* op = reinterpret_cast<const float*>(smem + SM_OPART) + lane;
                const float4* ml = reinterpret_cast<const float4*>(smem + SM_ML);
                const float4 e0 = ml[0], e1 = ml[1], e2 = ml[2], e3 = ml[3];
                const float M = fmaxf(fmaxf(fmaxf(e0.x, e0.z), fmaxf(e1.x, e1.z)), fmaxf(fmaxf(e2.x, e2.z), fmaxf(e3.x, e3.z)));
                const float f0 = __expf(e0.x - M), f1 = __expf(e0.z - M), f2 = __expf(e1.x - M), f3 = __expf(e1.z - M);
                const float f4 = __expf(e2.x - M), f5 = __expf(e2.z - M), f6 = __expf(e3.x - M), f7 = __expf(e3.z - M);
                const float l = ((f0 * e0.y + f1 * e0.w) + (f2 * e1.y + f3 * e1.w)) + ((f4 * e2.y + f5 * e2.w) + (f6 * e3.y + f7 * e3.w));
                float o = ((f0 * op[0] + f1 * op[32]) + (f2 * op[64] + f3 * op[96])) + ((f4 * op[128] + f5 * op[160]) + (f6 * op[192] + f7 * op[224]));
                o *= fast_rcp(l);
                if (ct == 0) TLD(4, o);
                const unsigned pr = pack_bf(o, __shfl_down_sync(FULL, o, 1));
                unsigned bf[4];
#pragma unroll
                for (int s = 0; s < 4; s++) bf[s] = __shfl_sync(FULL, pr, 8 * s + 2 * t);
#pragma unroll 1
                for (int n = 0; n < SPIN_LIMIT; n++) {
                    if (!__any_sync(FULL, (sd0 & sd1 & tag) == 0)) break;
                    __nanosleep(100);
                    sd0 = ld_w1(sd_src); sd1 = ld_w1(sd_src + 8);
                }
                c1_a = pin(scr + near_off(PR_C1 + oct, sd0 >> 2) + b * 8 + g);
                c1_b = pin(scr + near_off(PR_C1 + oct + 1, sd1 >> 2) + b * 8 + g);
                d_a = pin(scr + near_off(PR_D + oct, sd0 >> 2) + b * 8 + g);
                d_b = pin(scr + near_off(PR_D + oct + 1, sd1 >> 2) + b * 8 + g);
                if (ct == 0) TL(29);
                float y[4][4];
#pragma unroll
                for (int j = 0; j < 4; j++) y[j][0] = y[j][1] = y[j][2] = y[j][3] = 0.f;
#pragma unroll
                for (int s = 0; s < 2; s++) {
                    mbar_wait(bars + (BAR_WO + s) * 8, lim);
                    uint4 a[4];
#pragma unroll
                    for (int j = 0; j < 4; j++) a[j] = ldsm4t(sb + SM_WO + s * 16 * ROW_PITCH + rowoff + j * 32);
#pragma unroll
                    for (int j = 0; j < 4; j++) mma16816(y[j], a[j].x, a[j].y, a[j].z, a[j].w, bf[2 * s], bf[2 * s + 1]);
                }
                st_w1_p(c1_a, tagw(sel4(y[0][0], y[1][0], y[2][0], y[3][0], t), tag), real);
                st_w1_p(c1_b, tagw(sel4(y[0][2], y[1][2], y[2][2], y[3][2], t), tag), real);
                if (ct == 0) TL(6);
            }
            if (b >= NFFN) {
                if (real) return;
                real = 1;
                continue;
            }

            uint4 a[4];
            mbar_wait(bars + (BAR_W1 + (cw >> 1)) * 8, lim);
            {
                const uint32_t ab = sb + SM_W1 + (64 * cw + (mi >> 1) * 8 + ri) * 32 + (((mi & 1) ^ (ri >> 2)) * 16);
#pragma unroll
                for (int s = 0; s < 4; s++) a[s] = ldsm4t(ab + s * 512);
            }
            const uint32_t part_w = sb + SM_CSP + ((g + 8 * (t & 1)) * 12 + cw) * 4;
            {
                float cs[4] = {0.f, 0.f, 0.f, 0.f};
#pragma unroll
                for (int s = 0; s < 4; s++) mma16816(cs, a[s].x, a[s].y, a[s].z, a[s].w, 0x3F803F80u, 0x3F803F80u);
                sts_p(part_w, selp(cs[2], cs[0], t & 1), real && t < 2);
            }
            if (ct == 0) TL(7);
            bar_sync_p<NB_CS, 320>(real);
            float cs0, cs1, cs2, cs3;
            {
                const float4* const cs_r = reinterpret_cast<const float4*>(smem + SM_CSP + (lane & 15) * 48);
                const float4 u0 = cs_r[0], u1 = cs_r[1];
                const float2 u2 = *reinterpret_cast<const float2*>(cs_r + 2);
                const float cs = ((u0.x + u0.y) + (u0.z + u0.w)) + ((u1.x + u1.y) + (u1.z + u1.w)) + (u2.x + u2.y);
                cs0 = __shfl_sync(FULL, cs, 2 * t); cs1 = __shfl_sync(FULL, cs, 2 * t + 1);
                cs2 = __shfl_sync(FULL, cs, 2 * t + 8); cs3 = __shfl_sync(FULL, cs, 2 * t + 9);
            }
            uint32_t dp_w = (t < 2) ? part_w + 768 : sb + SM_DP + (14 + t) * 48 + cw * 4;
            uint32_t dp_r = sb + SM_DP + min(lane, 17) * 48;
            uint32_t w2_r = sb + SM_W2 + rowoff;
            unsigned do_w = real && ((t < 2) || (g == 0));
            asm volatile("" : "+r"(dp_w), "+r"(dp_r), "+r"(w2_r), "+r"(do_w));
            mbar_wait(bars + BAR_SIG * 8, (b < NOCT) ? lim : 0);
            uint2 hv = make_uint2(tag, tag);
            if (real) hv = ld_w2(h_src);
            uint4 w[4];
            const bool w2_early = mbar_test(bars + BAR_W2 * 8);
            if (w2_early) {
#pragma unroll
                for (int j = 0; j < 4; j++) w[j] = ldsm4t(w2_r + j * 32);
            }
#pragma unroll 1
            for (int n = 0; n < SPIN_LIMIT; n++) {
                if (!__any_sync(FULL, bad2(hv, tag))) break;
                hv = ld_w2(h_src);
            }
            const unsigned hpair = __byte_perm(hv.x, hv.y, 0x7632);
            if (ct == 0) TL(8);
            unsigned hf[8];
#pragma unroll
            for (int s = 0; s < 8; s++) hf[s] = __shfl_sync(FULL, hpair, 4 * s + t);
            float dA[4] = {0.f, 0.f, 0.f, 0.f}, dB[4] = {0.f, 0.f, 0.f, 0.f}, sA[4] = {0.f, 0.f, 0.f, 0.f}, sB[4] = {0.f, 0.f, 0.f, 0.f};
#pragma unroll
            for (int s = 0; s < 4; s += 2) {
                mma16816(dA, a[s].x, a[s].y, a[s].z, a[s].w, hf[2 * s], hf[2 * s + 1]);
                mma16816(dB, a[s + 1].x, a[s + 1].y, a[s + 1].z, a[s + 1].w, hf[2 * s + 2], hf[2 * s + 3]);
                mma16816(sA, hf[2 * s], 0x3F803F80u, hf[2 * s + 1], 0x3F803F80u, hf[2 * s], hf[2 * s + 1]);
                mma16816(sB, hf[2 * s + 2], 0x3F803F80u, hf[2 * s + 3], 0x3F803F80u, hf[2 * s + 2], hf[2 * s + 3]);
            }
            sts_p(dp_w, sel4(dA[0] + dB[0], dA[2] + dB[2], sA[0] + sB[0], sA[2] + sB[2], t), do_w);
            bar_sync_p<NB_FPART, 320>(real);
            const uint4 u0 = lds16(dp_r), u1 = lds16(dp_r + 16);
            float u2x, u2y;
            asm volatile("ld.shared.v2.f32 {%0,%1}, [%2];" : "=f"(u2x), "=f"(u2y) : "r"(dp_r + 32) : "memory");
            if (!w2_early) {
                mbar_wait(bars + BAR_W2 * 8, lim);
#pragma unroll
                for (int j = 0; j < 4; j++) w[j] = ldsm4t(w2_r + j * 32);
            }
            if (ct == 0) TLD(21, u2x);
            const float dot = ((__uint_as_float(u0.x) + __uint_as_float(u0.y)) + (__uint_as_float(u0.z) + __uint_as_float(u0.w))) +
                              ((__uint_as_float(u1.x) + __uint_as_float(u1.y)) + (__uint_as_float(u1.z) + __uint_as_float(u1.w))) + (u2x + u2y);
            const float sm = __shfl_sync(FULL, dot, 17), sq = __shfl_sync(FULL, dot, 16);
            const float d0 = __shfl_sync(FULL, dot, 2 * t), d1 = __shfl_sync(FULL, dot, 2 * t + 1);
            const float d2 = __shfl_sync(FULL, dot, 2 * t + 8), d3 = __shfl_sync(FULL, dot, 2 * t + 9);
            const float mean = sm * (1.0f / 640.0f);
            const float m2 = bfr(mean);
            const unsigned b0 = pack_bf(fmaxf(fmaf(-m2, cs0, d0), 0.f), fmaxf(fmaf(-m2, cs1, d1), 0.f));
            const unsigned b1 = pack_bf(fmaxf(fmaf(-m2, cs2, d2), 0.f), fmaxf(fmaf(-m2, cs3, d3), 0.f));
            float y[4][4];
#pragma unroll
            for (int j = 0; j < 4; j++) {
                y[j][0] = y[j][1] = y[j][2] = y[j][3] = 0.f;
                mma16816(y[j], w[j].x, w[j].y, w[j].z, w[j].w, b0, b1);
            }
            const float var = fmaxf(fmaf(-mean, mean, sq * (1.0f / 640.0f)), 0.f);
            const float rinv = fast_rcp(bfr(fast_sqrt(bfr(bfr(var) + 1e-5f))));
            st_w1_p(d_a, tagw(rinv * sel4(y[0][0], y[1][0], y[2][0], y[3][0], t), tag), real);
            st_w1_p(d_b, tagw(rinv * sel4(y[0][2], y[1][2], y[2][2], y[3][2], t), tag), real);
            if (ct == 0) TL(9);
            bar_arrive_p<NB_DSENT, 352>(real && b < NOCT);
            if (real) return;
            real = 1;
        }
    } else if (warp == 1) {
        const unsigned t0 = tstart + (unsigned)((h & 7) * pc.stag);
        if (lane == 0) {
            TLV(0, tstart);
#pragma unroll
            for (int i = 0; i < NBAR; i++) mbar_init(bars + i * 8, 1);
            asm volatile("fence.mbarrier_init.release.cluster;" ::: "memory");
            asm volatile("prefetch.tensormap [%0];" :: "l"(&map_v) : "memory");
            asm volatile("prefetch.tensormap [%0];" :: "l"(&map_w1) : "memory");
        }
        bar_arrive(NB_XN, N_XN);
        if (lane == 0) {
            int tt = pc.tK;
            const char* ks = reinterpret_cast<const char*>(kc) + (size_t)h * 1048576 + 786432 + c * 65536;
#pragma unroll 1
            for (int ii = 0; ii < 16; ii++) {
                const int i = (ii + h * pc.rotK) & 15;
                wait_until(t0, tt); tt += pc.dKV;
                mbar_expect_tx(bars + (BAR_K + i) * 8, 4096);
                bulk_g2s(sb + SM_K + i * 4096, ks + i * 4096, 4096, bars + (BAR_K + i) * 8);
            }
#pragma unroll 1
            for (int ii = 0; ii < 16; ii++) {
                const int i = (ii + h * pc.rotV) & 15;
                wait_until(t0, tt); tt += pc.dKV;
                mbar_expect_tx(bars + (BAR_V + i) * 8, 4096);
                tma2d(sb + SM_V + i * 4096, &map_v, 32 * c, h * 4096 + 3072 + 64 * i, bars + (BAR_V + i) * 8);
            }
            {
                const char* ws = reinterpret_cast<const char*>(wo) + (size_t)b * 32 * 1280;
                mbar_expect_tx(bars + BAR_WO * 8, 16 * 1280);
                mbar_expect_tx(bars + (BAR_WO + 1) * 8, 16 * 1280);
#pragma unroll 1
                for (int j = 0; j < 8; j++) {
                    wait_until(t0, tt); tt += pc.dWO;
#pragma unroll
                    for (int i = 0; i < 4; i++) {
                        const int r = j * 4 + i;
                        bulk_g2s(sb + SM_WO + r * ROW_PITCH, ws + r * 1280, 1280, bars + (BAR_WO + (j >> 2)) * 8);
                    }
                }
                tt += pc.gap;
            }
            if (b < NFFN) {
#pragma unroll 1
                for (int j = 0; j < 5; j++) {
                    wait_until(t0, tt); tt += pc.dW1;
                    mbar_expect_tx(bars + (BAR_W1 + j) * 8, 4096);
                    tma2d(sb + SM_W1 + j * 4096, &map_w1, 16 * b, 128 * j, bars + (BAR_W1 + j) * 8);
                }
                const char* w2s = reinterpret_cast<const char*>(w2) + (size_t)b * 16 * 1280;
                mbar_expect_tx(bars + BAR_W2 * 8, 16 * 1280);
#pragma unroll 1
                for (int j = 0; j < 4; j++) {
                    wait_until(t0, tt); tt += pc.dW2;
#pragma unroll
                    for (int i = 0; i < 4; i++) {
                        const int r = j * 4 + i;
                        bulk_g2s(sb + SM_W2 + r * ROW_PITCH, w2s + r * 1280, 1280, bars + BAR_W2 * 8);
                    }
                }
                TL(10);
            }
            if (pc.mode == 1) {
                const int nb = (b < NFFN) ? BAR_SIG : BAR_W1;
                for (int i = 0; i < nb; i++) mbar_wait(bars + i * 8);
            }
        }
    } else {
        const int col = 8 * b + 4 * (lane & 1) + (lane & 2) + ((lane >> 2) & 1);
        float base = 0.f;
        if (b < NOCT) base = __bfloat162float(x[col]);
        {
            float s = 0.f;
#pragma unroll
            for (int j = 0; j < 5; j++) s += (bf_lo(xr[j].x) + bf_hi(xr[j].x)) + (bf_lo(xr[j].y) + bf_hi(xr[j].y));
#pragma unroll
            for (int o = 16; o; o >>= 1) s += __shfl_xor_sync(FULL, s, o);
            const float mean = s * (1.0f / 640.0f);
            float v = 0.f;
#pragma unroll
            for (int j = 0; j < 5; j++) {
                float d0 = bf_lo(xr[j].x) - mean, d1 = bf_hi(xr[j].x) - mean, d2 = bf_lo(xr[j].y) - mean, d3 = bf_hi(xr[j].y) - mean;
                v += (d0 * d0 + d1 * d1) + (d2 * d2 + d3 * d3);
            }
#pragma unroll
            for (int o = 16; o; o >>= 1) v += __shfl_xor_sync(FULL, v, o);
            const float mb = bfr(mean);
            const float rb = __frcp_rn(bfr(__fsqrt_rn(bfr(bfr(v * (1.0f / 640.0f)) + 1e-5f))));
            float4* xn = reinterpret_cast<float4*>(smem + SM_XN);
#pragma unroll
            for (int j = 0; j < 5; j++) {
                float4 o;
                o.x = bfr(bfr(bf_lo(xr[j].x) - mb) * rb); o.y = bfr(bfr(bf_hi(xr[j].x) - mb) * rb);
                o.z = bfr(bfr(bf_lo(xr[j].y) - mb) * rb); o.w = bfr(bfr(bf_hi(xr[j].y) - mb) * rb);
                xn[j * 32 + lane] = o;
            }
        }
        const unsigned tag = 1u + (epoch & 1u);
        if (lane == 0) misc[0] = tag;
        if (lane == 0) TL(22);
        bar_sync(NB_XN, N_XN);
        bar_arrive(NB_TAG0, 64);
        bar_arrive(NB_TAG1, 64);
        unsigned* const a_dst = scr + PR_A * PAIR_W + b * 128 + 4 * lane;
        unsigned* const h_dst = pin(scr + PR_H * PAIR_W + (lane >> 3) * REP_W + col);
        st_w4(a_dst, make_uint4(0u, 0u, 0u, 0u));
        if (b < NOCT) st_w1(h_dst, 0u);
        bar_sync(NB_QPART, 288);
        {
            const float4* qp = reinterpret_cast<const float4*>(smem + SM_QPART) + lane;
            float4 s = qp[0];
            if (lane == 0) TLD(1, s.x);
#pragma unroll
            for (int w = 1; w < 8; w++) { const float4 u = qp[w * 32]; s.x += u.x; s.y += u.y; s.z += u.z; s.w += u.w; }
            const uint4 mine = make_uint4(tagw(s.x, tag), tagw(s.y, tag), tagw(s.z, tag), tagw(s.w, tag));
            st_w4(a_dst, mine);
            if (pc.mode == 1) return;
            const unsigned* pa = scr + PR_A * PAIR_W + h * 512 + 4 * lane;
            __nanosleep(300);
            uint4 v[4];
#pragma unroll 1
            for (int n = 0; n < SPIN_LIMIT; n++) {
#pragma unroll
                for (int cc = 0; cc < 4; cc++) v[cc] = (cc == c) ? mine : ld_w4(pa + cc * 128);
                if (!__any_sync(FULL, bad4(v[0], tag) | bad4(v[1], tag) | bad4(v[2], tag) | bad4(v[3], tag))) break;
                __nanosleep(100);
            }
            const float q0 = ((untag(v[0].x) + untag(v[1].x)) + untag(v[2].x)) + untag(v[3].x);
            const float q1 = ((untag(v[0].y) + untag(v[1].y)) + untag(v[2].y)) + untag(v[3].y);
            const float q2 = ((untag(v[0].z) + untag(v[1].z)) + untag(v[2].z)) + untag(v[3].z);
            const float q3 = ((untag(v[0].w) + untag(v[1].w)) + untag(v[2].w)) + untag(v[3].w);
            reinterpret_cast<uint2*>(smem + SM_QS)[lane] = make_uint2(pack_bf(q0, q1), pack_bf(q2, q3));
        }
        bar_arrive(NB_Q, 288);
        if (lane == 0) TL(2);
        if (b >= NOCT) return;
        mbar_wait(bars + BAR_CLR * 8);
        const unsigned side = misc[1];
        const unsigned* src = pin(scr + near_off(PR_C1 + b, side) + 4 * lane);
        const unsigned* const d_src = pin(scr + near_off(PR_D + b, side) + 4 * lane);
        __nv_bfloat16* const o_dst = pin(out + col);
        int lane_p = lane, dly_d = pc.dlyD;
        asm volatile("" : "+r"(lane_p), "+r"(dly_d));
#pragma unroll 1
        for (int phase = (pc.dry & 2) ? 0 : 1; phase < 3; phase++) {
            asm volatile("" : "+r"(phase));
            mbar_wait(bars + (BAR_WO + 1) * 8, phase == 1 ? SPIN_LIMIT : 0);
            bar_sync_p<NB_DSENT, 352>(phase == 2);
            spin_cycles(phase == 2 ? dly_d : 0);
            uint4 v[8];
#pragma unroll
            for (int j = 0; j < 8; j++) { v[j] = make_uint4(tag, tag, tag, tag); if (phase) v[j] = ld_w4(src + 128 * j); }
            float r = 0.f;
#pragma unroll 1
            for (int n = 0; n < SPIN_LIMIT; n++) {
                float t0 = ((__uint_as_float(v[0].x) + __uint_as_float(v[1].x)) + (__uint_as_float(v[2].x) + __uint_as_float(v[3].x))) +
                           ((__uint_as_float(v[4].x) + __uint_as_float(v[5].x)) + (__uint_as_float(v[6].x) + __uint_as_float(v[7].x)));
                float t1 = ((__uint_as_float(v[0].y) + __uint_as_float(v[1].y)) + (__uint_as_float(v[2].y) + __uint_as_float(v[3].y))) +
                           ((__uint_as_float(v[4].y) + __uint_as_float(v[5].y)) + (__uint_as_float(v[6].y) + __uint_as_float(v[7].y)));
                float t2 = ((__uint_as_float(v[0].z) + __uint_as_float(v[1].z)) + (__uint_as_float(v[2].z) + __uint_as_float(v[3].z))) +
                           ((__uint_as_float(v[4].z) + __uint_as_float(v[5].z)) + (__uint_as_float(v[6].z) + __uint_as_float(v[7].z)));
                float t3 = ((__uint_as_float(v[0].w) + __uint_as_float(v[1].w)) + (__uint_as_float(v[2].w) + __uint_as_float(v[3].w))) +
                           ((__uint_as_float(v[4].w) + __uint_as_float(v[5].w)) + (__uint_as_float(v[6].w) + __uint_as_float(v[7].w)));
                asm volatile("" : "+f"(t0), "+f"(t1), "+f"(t2), "+f"(t3));
                bool miss = false;
#pragma unroll
                for (int j = 0; j < 8; j++)
                    if (bad4(v[j], tag)) { v[j] = ld_w4(src + 128 * j); miss = true; }
                const bool again = __any_sync(FULL, miss);
                r = octet_reduce(t0, t1, t2, t3, lane_p);
                if (!again) break;
            }
            const float res = bfr(base + bfr(r));
            st_w1_p(h_dst, __float_as_uint(res) | tag, phase == 1);
            asm volatile("{\n.reg .pred p;\nsetp.ne.u32 p, %2, 0;\n@p st.global.u16 [%0], %1;\n}"
                         :: "l"(o_dst), "h"((unsigned short)(__float_as_uint(res) >> 16)), "r"((unsigned)(phase == 2 && lane_p < 8)) : "memory");
            mbar_arrive_p(bars + BAR_SIG * 8, phase == 1 && lane_p == 0);
            if (lane_p == 0) TL(phase == 2 ? 13 : phase == 1 ? 12 : 31);
            if (phase == 1) { base = res; src = d_src; }
        }
        if (b == 0 && lane == 0) st_w1(scr + PR_EPOCH * PAIR_W, epoch + 1u);
    }
}

Pace g_pace = {1150, 165, 206, 139, 174, 20, 200, 200, 4, 8, 600, 0, 0, 0, 0};
unsigned* g_scr_base = nullptr;
int g_w1_promo = 2;
int g_v_promo = 2;

}

typedef CUresult (*EncodeTiledFn)(CUtensorMap*, CUtensorMapDataType, cuuint32_t, void*, const cuuint64_t*, const cuuint64_t*,
                                  const cuuint32_t*, const cuuint32_t*, CUtensorMapInterleave, CUtensorMapSwizzle,
                                  CUtensorMapL2promotion, CUtensorMapFloatOOBfill);

extern "C" void kernel_launch(void* const* d_in, const int* in_sizes, int n_in, void* d_out, int out_size) {
    (void)in_sizes; (void)n_in; (void)out_size;
    static EncodeTiledFn encode = nullptr;
    if (!encode) {
        cudaFuncSetAttribute(fk::fused_decode_kernel, cudaFuncAttributeMaxDynamicSharedMemorySize, fk::SMEM_BYTES);
        void* fn = nullptr;
        cudaDriverEntryPointQueryResult qres;
        cudaGetDriverEntryPoint("cuTensorMapEncodeTiled", &fn, cudaEnableDefault, &qres);
        encode = (EncodeTiledFn)fn;
        void* sp = nullptr;
        cudaGetSymbolAddress(&sp, fk::g_scr);
        fk::g_scr_base = (unsigned*)(((uintptr_t)sp + (2u << 20) - 1) & ~(uintptr_t)((2u << 20) - 1));
    }
    CUtensorMap map_v, map_w1;
    {
        const cuuint64_t dims[2] = {128, 32 * 4096}, strides[1] = {256};
        const cuuint32_t box[2] = {32, 64}, es[2] = {1, 1};
        encode(&map_v, CU_TENSOR_MAP_DATA_TYPE_BFLOAT16, 2, d_in[2], dims, strides, box, es, CU_TENSOR_MAP_INTERLEAVE_NONE,
               CU_TENSOR_MAP_SWIZZLE_64B, (CUtensorMapL2promotion)fk::g_v_promo, CU_TENSOR_MAP_FLOAT_OOB_FILL_NONE);
    }
    {
        const cuuint64_t dims[2] = {1728, 640}, strides[1] = {3456};
        const cuuint32_t box[2] = {16, 128}, es[2] = {1, 1};
        encode(&map_w1, CU_TENSOR_MAP_DATA_TYPE_BFLOAT16, 2, d_in[6], dims, strides, box, es, CU_TENSOR_MAP_INTERLEAVE_NONE,
               CU_TENSOR_MAP_SWIZZLE_32B, (CUtensorMapL2promotion)fk::g_w1_promo, CU_TENSOR_MAP_FLOAT_OOB_FILL_NONE);
    }
    fk::fused_decode_kernel<<<fk::NCTA, fk::NTHREADS, fk::SMEM_BYTES>>>(
        (const __nv_bfloat16*)d_in[0], (const __nv_bfloat16*)d_in[3], (const __nv_bfloat16*)d_in[1],
        (const __nv_bfloat16*)d_in[4], (const __nv_bfloat16*)d_in[7], (__nv_bfloat16*)d_out, fk::g_scr_base, fk::g_pace, map_v, map_w1);
}
```

```cpp
#include <cuda_runtime.h>
#include <cuda.h>
#include <cuda_bf16.h>
#include <stdint.h>
#include <stdlib.h>

namespace fk {

constexpr int NCTA = 128;
constexpr int NFFN = 108;
constexpr int NOCT = 80;
constexpr int NWO = 80;
constexpr int NTHREADS = 384;

constexpr int ROW_PITCH = 1296;
constexpr int SM_K = 0;
constexpr int SM_V = 65536;
constexpr int SM_W1 = 131072;
constexpr int SM_W2 = SM_W1 + 640 * 32;
constexpr int SM_QPART = SM_W2 + 16 * ROW_PITCH;
constexpr int SM_P = SM_QPART + 4096;
constexpr int SM_XN = SM_P + 576;
constexpr int SM_ML = SM_XN + 2560;
constexpr int SM_QS = SM_ML + 64;
constexpr int SM_HP = SM_QS + 256;
constexpr int SM_DP = SM_HP + 768;
constexpr int SM_H1 = SM_DP + 34 * 48;
constexpr int SM_OF = SM_H1 + 32;
constexpr int SM_TAG = SM_OF + 16 * 144;
constexpr int SM_BAR = SM_TAG + 32;
constexpr int BAR_K = 0, BAR_V = 16, BAR_WO = 32, BAR_W1 = 40, BAR_W2 = 45, BAR_SIDE = 46, BAR_CLR = 47, BAR_KFREE = 48, NBAR = 49;
constexpr int SMEM_BYTES = SM_BAR + NBAR * 8;

constexpr int SPIN_LIMIT = 1 << 20;
#define NPRE 5
#define NTRIG 2

struct Pace {
    int tK;
    int dKV;
    int dWO;
    int dW1;
    int dW2;
    int stag;
    int gap;
    int dlyD;
    int sV;
    int nprobe;
    int tP;
    int mode;
    int early;
    int npre;
    int dlyO;
    int slp;
    int tH;
};

__device__ __align__(4096) unsigned g_scr[1 << 20];
constexpr int PAIR_W = 2048, REP_W = 1024;
constexpr int PR_D = 0;
constexpr int PR_H = 172;
constexpr int PR_O = 88;
constexpr int PR_A = 120;
constexpr int PR_SIDE = 136;
constexpr int PR_PROBE = 137;
constexpr int PR_EPOCH = 169;
constexpr int PR_TL = 170;
__device__ __forceinline__ int near_off(int pair, unsigned side) {
    return pair * PAIR_W + (int)((side ^ __popc((2 * pair) & 0xb3)) & 1u) * REP_W;
}
#define TL(i) do {} while (0)
#define TLD(i, v) do {} while (0)
#define TLV(i, v) do {} while (0)

__device__ __forceinline__ unsigned gtime32() {
    unsigned long long t; asm volatile("mov.u64 %0, %globaltimer;" : "=l"(t) :: "memory"); return (unsigned)t;
}
__device__ __forceinline__ uint32_t smem_u32(const void* p) { return (uint32_t)__cvta_generic_to_shared(p); }
__device__ __forceinline__ void mbar_init(uint32_t bar, uint32_t cnt) {
    asm volatile("mbarrier.init.shared::cta.b64 [%0], %1;" :: "r"(bar), "r"(cnt) : "memory");
}
__device__ __forceinline__ void mbar_expect_tx(uint32_t bar, uint32_t bytes) {
    asm volatile("mbarrier.arrive.expect_tx.shared::cta.b64 _, [%0], %1;" :: "r"(bar), "r"(bytes) : "memory");
}
__device__ __forceinline__ void mbar_arrive(uint32_t bar) {
    asm volatile("mbarrier.arrive.shared::cta.b64 _, [%0];" :: "r"(bar) : "memory");
}
__device__ __forceinline__ void mbar_arrive_p(uint32_t bar, unsigned p) {
    asm volatile("{\n.reg .pred p;\nsetp.ne.u32 p, %1, 0;\n@p mbarrier.arrive.shared::cta.b64 _, [%0];\n}" :: "r"(bar), "r"(p) : "memory");
}
__device__ __forceinline__ bool mbar_test(uint32_t bar) {
    uint32_t ok;
    asm volatile("{\n.reg .pred p;\nmbarrier.test_wait.parity.shared::cta.b64 p, [%1], 0;\nselp.u32 %0, 1, 0, p;\n}"
                 : "=r"(ok) : "r"(bar) : "memory");
    return ok != 0;
}
__device__ __forceinline__ bool mbar_try(uint32_t bar) {
    uint32_t ok;
    asm volatile("{\n.reg .pred p;\nmbarrier.try_wait.parity.shared::cta.b64 p, [%1], 0;\nselp.u32 %0, 1, 0, p;\n}"
                 : "=r"(ok) : "r"(bar) : "memory");
    return ok != 0;
}
__device__ __forceinline__ void mbar_wait(uint32_t bar, int lim = SPIN_LIMIT) {
#pragma unroll 1
    for (int n = 0; n < lim; n++) if (mbar_try(bar)) break;
}
__device__ __forceinline__ void bulk_g2s(uint32_t dst, const void* src, uint32_t bytes, uint32_t bar) {
    asm volatile("cp.async.bulk.shared::cluster.global.mbarrier::complete_tx::bytes [%0], [%1], %2, [%3];"
                 :: "r"(dst), "l"(src), "r"(bytes), "r"(bar) : "memory");
}
__device__ __forceinline__ void tma3d(uint32_t dst, const CUtensorMap* map, int c0, int c1, int c2, uint32_t bar) {
    asm volatile("cp.async.bulk.tensor.3d.shared::cluster.global.mbarrier::complete_tx::bytes [%0], [%1, {%3, %4, %5}], [%2];"
                 :: "r"(dst), "l"(map), "r"(bar), "r"(c0), "r"(c1), "r"(c2) : "memory");
}
__device__ __forceinline__ void tma2d(uint32_t dst, const CUtensorMap* map, int c0, int c1, uint32_t bar) {
    asm volatile("cp.async.bulk.tensor.2d.shared::cluster.global.mbarrier::complete_tx::bytes [%0], [%1, {%3, %4}], [%2];"
                 :: "r"(dst), "l"(map), "r"(bar), "r"(c0), "r"(c1) : "memory");
}
__device__ __forceinline__ unsigned tagw(float v, unsigned tag) { return (__float_as_uint(v) & ~3u) | tag; }
__device__ __forceinline__ float untag(unsigned w) { return __uint_as_float(w & ~3u); }
__device__ __forceinline__ void st_w1(unsigned* p, unsigned a) {
    asm volatile("st.relaxed.gpu.global.u32 [%0], %1;" :: "l"(p), "r"(a) : "memory");
}
__device__ __forceinline__ void st_w1_p(unsigned* a, unsigned v, unsigned p) {
    asm volatile("{\n.reg .pred p;\nsetp.ne.u32 p, %2, 0;\n@p st.relaxed.gpu.global.u32 [%0], %1;\n}" :: "l"(a), "r"(v), "r"(p) : "memory");
}
__device__ __forceinline__ void st_w4(unsigned* p, uint4 v) {
    asm volatile("st.relaxed.gpu.global.v4.u32 [%0], {%1,%2,%3,%4};" :: "l"(p), "r"(v.x), "r"(v.y), "r"(v.z), "r"(v.w) : "memory");
}
__device__ __forceinline__ unsigned ld_w1(const unsigned* p) {
    unsigned v;
    asm volatile("ld.relaxed.gpu.global.u32 %0, [%1];" : "=r"(v) : "l"(p) : "memory");
    return v;
}
__device__ __forceinline__ uint4 ld_w4(const unsigned* p) {
    uint4 v;
    asm volatile("ld.relaxed.gpu.global.v4.u32 {%0,%1,%2,%3}, [%4];" : "=r"(v.x), "=r"(v.y), "=r"(v.z), "=r"(v.w) : "l"(p) : "memory");
    return v;
}
__device__ __forceinline__ uint2 ld_w2(const unsigned* p) {
    uint2 v;
    asm volatile("ld.relaxed.gpu.global.v2.u32 {%0,%1}, [%2];" : "=r"(v.x), "=r"(v.y) : "l"(p) : "memory");
    return v;
}
__device__ __forceinline__ bool bad2(uint2 v, unsigned tag) { return (v.x & v.y & tag) == 0; }
__device__ __forceinline__ bool bad4(uint4 v, unsigned tag) { return ((v.x & v.y & v.z) & v.w & tag) == 0; }

__device__ __forceinline__ void bar_sync(int id, int n) { __syncwarp(); asm volatile("bar.sync %0, %1;" :: "r"(id), "r"(n) : "memory"); }
__device__ __forceinline__ void bar_arrive(int id, int n) { __syncwarp(); asm volatile("bar.arrive %0, %1;" :: "r"(id), "r"(n) : "memory"); }
template <int ID, int N> __device__ __forceinline__ void bar_sync_p(unsigned p) {
    __syncwarp();
    asm volatile("{\n.reg .pred p;\nsetp.ne.u32 p, %0, 0;\n@p bar.sync %1, %2;\n}" :: "r"(p), "n"(ID), "n"(N) : "memory");
}
template <int ID, int N> __device__ __forceinline__ void bar_arrive_p(unsigned p) {
    __syncwarp();
    asm volatile("{\n.reg .pred p;\nsetp.ne.u32 p, %0, 0;\n@p bar.arrive %1, %2;\n}" :: "r"(p), "n"(ID), "n"(N) : "memory");
}
__device__ __forceinline__ void sts_p(uint32_t a, float v, unsigned p) {
    asm volatile("{\n.reg .pred p;\nsetp.ne.u32 p, %2, 0;\n@p st.shared.f32 [%0], %1;\n}" :: "r"(a), "f"(v), "r"(p) : "memory");
}
__device__ __forceinline__ float bf_lo(unsigned u) { return __uint_as_float(u << 16); }
__device__ __forceinline__ float bf_hi(unsigned u) { return __uint_as_float(u & 0xffff0000u); }
__device__ __forceinline__ unsigned pack_bf(float lo, float hi) {
    unsigned r; asm("cvt.rn.bf16x2.f32 %0, %1, %2;" : "=r"(r) : "f"(hi), "f"(lo)); return r;
}
__device__ __forceinline__ float bfr(float v) { return __uint_as_float(pack_bf(0.f, v)); }
__device__ __forceinline__ float selp(float a, float b, unsigned c) {
    float r; asm("{\n.reg .pred p;\nsetp.ne.u32 p, %3, 0;\nselp.f32 %0, %1, %2, p;\n}" : "=f"(r) : "f"(a), "f"(b), "r"(c)); return r;
}
__device__ __forceinline__ float sel4(float a0, float a1, float a2, float a3, int t) {
    return selp(selp(a3, a2, t & 1), selp(a1, a0, t & 1), t & 2);
}
__device__ __forceinline__ float fast_sqrt(float v) { float r; asm("sqrt.approx.ftz.f32 %0, %1;" : "=f"(r) : "f"(v)); return r; }
__device__ __forceinline__ float fast_rcp(float v) { float r; asm("rcp.approx.ftz.f32 %0, %1;" : "=f"(r) : "f"(v)); return r; }
template <class T> __device__ __forceinline__ T* pin(T* p) { asm volatile("" : "+l"(p)); return p; }
__device__ __forceinline__ void mma16816(float (&c)[4], unsigned a0, unsigned a1, unsigned a2, unsigned a3,
                                         unsigned b0, unsigned b1) {
    asm volatile("mma.sync.aligned.m16n8k16.row.col.f32.bf16.bf16.f32 {%0,%1,%2,%3}, {%4,%5,%6,%7}, {%8,%9}, {%0,%1,%2,%3};"
                 : "+f"(c[0]), "+f"(c[1]), "+f"(c[2]), "+f"(c[3])
                 : "r"(a0), "r"(a1), "r"(a2), "r"(a3), "r"(b0), "r"(b1));
}
__device__ __forceinline__ uint4 ldsm4t(uint32_t addr) {
    uint4 r;
    asm volatile("ldmatrix.sync.aligned.m8n8.x4.trans.shared.b16 {%0,%1,%2,%3}, [%4];"
                 : "=r"(r.x), "=r"(r.y), "=r"(r.z), "=r"(r.w) : "r"(addr) : "memory");
    return r;
}
__device__ __forceinline__ uint4 lds16(uint32_t addr) {
    uint4 r;
    asm volatile("ld.shared.v4.u32 {%0,%1,%2,%3}, [%4];" : "=r"(r.x), "=r"(r.y), "=r"(r.z), "=r"(r.w) : "r"(addr) : "memory");
    return r;
}
__device__ __forceinline__ void wait_until(unsigned t0, int t) {
#pragma unroll 1
    for (int n = 0; n < SPIN_LIMIT; n++) if ((int)(gtime32() - t0) >= t) break;
}
__device__ __forceinline__ void spin_cycles(int n) {
    if (n > 0) { const unsigned c0 = clock(); while ((int)(clock() - c0) < n) {} }
}
__device__ __forceinline__ float octet_reduce(float v0, float v1, float v2, float v3, int lane) {
    const unsigned FULL = 0xffffffffu;
    const unsigned b1 = lane & 2, b2 = lane & 4;
    float k0 = selp(v2, v0, b1), k1 = selp(v3, v1, b1);
    const float s0 = selp(v0, v2, b1), s1 = selp(v1, v3, b1);
    k0 += __shfl_xor_sync(FULL, s0, 2);
    k1 += __shfl_xor_sync(FULL, s1, 2);
    float k = selp(k1, k0, b2);
    const float s = selp(k0, k1, b2);
    k += __shfl_xor_sync(FULL, s, 4);
    k += __shfl_xor_sync(FULL, k, 8);
    k += __shfl_xor_sync(FULL, k, 16);
    return k;
}

constexpr int NB_XN = 1, NB_QPART = 2, NB_Q = 3, NB_ATT = 4, NB_FPART = 5, NB_DSENT = 6, NB_H1 = 7, NB_PROBE = 8, NB_TAG0 = 9, NB_TAG1 = 10, NB_HP = 11;
constexpr int N_XN = NTHREADS - 64;

__global__ void __launch_bounds__(NTHREADS, 1)
fused_decode_kernel(const __nv_bfloat16* __restrict__ x, const __nv_bfloat16* __restrict__ wq,
                    const __nv_bfloat16* __restrict__ kc,
                    const __nv_bfloat16* __restrict__ w2, __nv_bfloat16* __restrict__ out, unsigned* __restrict__ scr, const Pace pc,
                    const __grid_constant__ CUtensorMap map_v, const __grid_constant__ CUtensorMap map_w1,
                    const __grid_constant__ CUtensorMap map_wo) {
    extern __shared__ __align__(1024) unsigned char smem[];
    const unsigned tstart = gtime32();
    const int tid = threadIdx.x, warp = tid >> 5, lane = tid & 31;
    const int b = blockIdx.x, h = b >> 2, c = b & 3;
    const int cw = warp - 2, ct = tid - 64;

    uint2 xr[5];
    unsigned epoch;
    uint4 wr[10];
    {
        const char* wp = reinterpret_cast<const char*>(wq) + (size_t)(160 * c + (ct >> 4)) * 8192 + h * 256 + (ct & 15) * 16;
        const uint2* xp = reinterpret_cast<const uint2*>(x) + lane;
        asm volatile("{\n.reg .pred p;\nsetp.ne.u32 p, %13, 0;\n@p bra.uni XSKIP;\n"
                     "ld.global.nc.v2.u32 {%0,%1}, [%11];\nld.global.nc.v2.u32 {%2,%3}, [%11+256];\nld.global.nc.v2.u32 {%4,%5}, [%11+512];\n"
                     "ld.global.nc.v2.u32 {%6,%7}, [%11+768];\nld.global.nc.v2.u32 {%8,%9}, [%11+1024];\n"
                     "ld.relaxed.gpu.global.u32 %10, [%12];\nXSKIP:\n}"
                     : "=r"(xr[0].x), "=r"(xr[0].y), "=r"(xr[1].x), "=r"(xr[1].y), "=r"(xr[2].x), "=r"(xr[2].y), "=r"(xr[3].x), "=r"(xr[3].y),
                       "=r"(xr[4].x), "=r"(xr[4].y), "=r"(epoch)
                     : "l"(xp), "l"(scr + PR_EPOCH * PAIR_W), "r"(warp) : "memory");
        asm volatile("{\n.reg .pred p;\nsetp.ge.u32 p, %41, 8;\n@p bra.uni WSKIP;\n"
                     "ld.global.nc.L1::no_allocate.v4.u32 {%0,%1,%2,%3}, [%40];\n"
                     "ld.global.nc.L1::no_allocate.v4.u32 {%4,%5,%6,%7}, [%40+131072];\n"
                     "ld.global.nc.L1::no_allocate.v4.u32 {%8,%9,%10,%11}, [%40+262144];\n"
                     "ld.global.nc.L1::no_allocate.v4.u32 {%12,%13,%14,%15}, [%40+393216];\n"
                     "ld.global.nc.L1::no_allocate.v4.u32 {%16,%17,%18,%19}, [%40+524288];\n"
                     "ld.global.nc.L1::no_allocate.v4.u32 {%20,%21,%22,%23}, [%40+655360];\n"
                     "ld.global.nc.L1::no_allocate.v4.u32 {%24,%25,%26,%27}, [%40+786432];\n"
                     "ld.global.nc.L1::no_allocate.v4.u32 {%28,%29,%30,%31}, [%40+917504];\n"
                     "ld.global.nc.L1::no_allocate.v4.u32 {%32,%33,%34,%35}, [%40+1048576];\n"
                     "ld.global.nc.L1::no_allocate.v4.u32 {%36,%37,%38,%39}, [%40+1179648];\n"
                     "WSKIP:\n}"
                     : "=r"(wr[0].x), "=r"(wr[0].y), "=r"(wr[0].z), "=r"(wr[0].w), "=r"(wr[1].x), "=r"(wr[1].y), "=r"(wr[1].z), "=r"(wr[1].w),
                       "=r"(wr[2].x), "=r"(wr[2].y), "=r"(wr[2].z), "=r"(wr[2].w), "=r"(wr[3].x), "=r"(wr[3].y), "=r"(wr[3].z), "=r"(wr[3].w),
                       "=r"(wr[4].x), "=r"(wr[4].y), "=r"(wr[4].z), "=r"(wr[4].w), "=r"(wr[5].x), "=r"(wr[5].y), "=r"(wr[5].z), "=r"(wr[5].w),
                       "=r"(wr[6].x), "=r"(wr[6].y), "=r"(wr[6].z), "=r"(wr[6].w), "=r"(wr[7].x), "=r"(wr[7].y), "=r"(wr[7].z), "=r"(wr[7].w),
                       "=r"(wr[8].x), "=r"(wr[8].y), "=r"(wr[8].z), "=r"(wr[8].w), "=r"(wr[9].x), "=r"(wr[9].y), "=r"(wr[9].z), "=r"(wr[9].w)
                     : "l"(wp), "r"(cw));
    }
    if (ct == 0) TL(15);

    const uint32_t sb = smem_u32(smem);
    const uint32_t bars = sb + SM_BAR;
    const int g = lane >> 2, t = lane & 3;
    const unsigned FULL = 0xffffffffu;
    volatile unsigned* const misc = reinterpret_cast<volatile unsigned*>(smem + SM_TAG);
    const int f = (b >= NWO) ? b - NWO : b + (NCTA - NWO);

    if ((unsigned)cw < 10u) {
        const int mi = lane >> 3, ri = lane & 7;
        unsigned tag, side, sd0, sd1;
        const int oct = 2 * (4 * cw + t);
        const unsigned xpair = __ldg(reinterpret_cast<const unsigned*>(x) + ct);
        if (cw < 8) {
            bar_sync(NB_XN, N_XN);
            tag = misc[0];
            unsigned* const o_dst = pin(scr + (PR_O + h) * PAIR_W + (t >> 1) * REP_W + c * 160 + 16 * cw + 8 * (t & 1) + g);
            unsigned* const ml_dst = scr + (PR_O + h) * PAIR_W + ((lane >> 3) & 1) * REP_W + c * 160 + 128 + (lane & 7);
            st_w1(o_dst, 0u);
            if (cw == 0 && lane < 16) st_w1(ml_dst, 0u);
            {
                const float* xn = reinterpret_cast<const float*>(smem + SM_XN) + 160 * c + (ct >> 4);
                float acc[8];
#pragma unroll
                for (int j = 0; j < 8; j++) acc[j] = 0.f;
#pragma unroll
                for (int i = 0; i < 10; i++) {
                    const float xv = xn[16 * i];
                    acc[0] = fmaf(xv, bf_lo(wr[i].x), acc[0]); acc[1] = fmaf(xv, bf_hi(wr[i].x), acc[1]);
                    acc[2] = fmaf(xv, bf_lo(wr[i].y), acc[2]); acc[3] = fmaf(xv, bf_hi(wr[i].y), acc[3]);
                    acc[4] = fmaf(xv, bf_lo(wr[i].z), acc[4]); acc[5] = fmaf(xv, bf_hi(wr[i].z), acc[5]);
                    acc[6] = fmaf(xv, bf_lo(wr[i].w), acc[6]); acc[7] = fmaf(xv, bf_hi(wr[i].w), acc[7]);
                }
#pragma unroll
                for (int j = 0; j < 8; j++) acc[j] += __shfl_xor_sync(FULL, acc[j], 16);
                if (lane < 16) {
                    float4* qp = reinterpret_cast<float4*>(smem + SM_QPART + cw * 512 + lane * 32);
                    qp[0] = make_float4(acc[0], acc[1], acc[2], acc[3]);
                    qp[1] = make_float4(acc[4], acc[5], acc[6], acc[7]);
                }
            }
            bar_arrive(NB_QPART, 288);
            if (pc.mode == 1) return;
            bar_sync(NB_Q, 288);
            uint4 qf[4];
#pragma unroll
            for (int j = 0; j < 4; j++) qf[j] = lds16(sb + SM_QS + 16 * (t + 4 * (j ^ (g & 1))));
            float mys = 0.f;
#pragma unroll 1
            for (int tile = 0; tile < 2; tile++) {
                const int ch = cw + 8 * tile;
                mbar_wait(bars + (BAR_K + ch) * 8);
                const uint32_t kb = sb + SM_K + ch * 4096 + g * 256 + t * 16;
                float cA[4] = {0.f, 0.f, 0.f, 0.f}, cB[4] = {0.f, 0.f, 0.f, 0.f};
#pragma unroll
                for (int j = 0; j < 4; j++) {
                    const uint32_t a = kb + 64 * (j ^ (g & 1));
                    const uint4 ra = lds16(a), rb = lds16(a + 2048);
                    mma16816(cA, ra.x, rb.x, ra.y, rb.y, qf[j].x, qf[j].y);
                    mma16816(cB, ra.z, rb.z, ra.w, rb.w, qf[j].z, qf[j].w);
                }
                const float s0 = selp(cA[1] + cB[1], cA[0] + cB[0], g & 1);
                const float s1 = selp(cA[3] + cB[3], cA[2] + cB[2], g & 1);
                mys = selp(selp(s1, s0, t & 1), mys, (t >> 1) == tile);
            }
            __syncwarp();
            if (lane == 0) mbar_arrive(bars + BAR_KFREE * 8);
            mys = bfr(bfr(mys) * 0.08838834764831845f);
            if (ct == 224) TL(3);
            {
                float* const ml = reinterpret_cast<float*>(smem + SM_ML);
                float m = mys;
#pragma unroll
                for (int o = 16; o; o >>= 1) m = fmaxf(m, __shfl_xor_sync(FULL, m, o));
                if (lane == 0) ml[cw] = m;
                bar_sync(NB_ATT, 256);
                const float4 m0 = reinterpret_cast<const float4*>(ml)[0], m1 = reinterpret_cast<const float4*>(ml)[1];
                m = fmaxf(fmaxf(fmaxf(m0.x, m0.y), fmaxf(m0.z, m0.w)), fmaxf(fmaxf(m1.x, m1.y), fmaxf(m1.z, m1.w)));
                const unsigned pb = pack_bf(__expf(mys - m), 0.f);
                *reinterpret_cast<unsigned short*>(smem + SM_P + (g >> 1) * 144 + (cw + 8 * (t >> 1)) * 8 + (t & 1) * 4 + (g & 1) * 2) = (unsigned short)pb;
                float l = bf_lo(pb);
#pragma unroll
                for (int o = 16; o; o >>= 1) l += __shfl_xor_sync(FULL, l, o);
                if (lane == 0) ml[8 + cw] = l;
                bar_sync(NB_ATT, 256);
                if (cw == 0) {
                    const float4 l0 = reinterpret_cast<const float4*>(ml)[2], l1 = reinterpret_cast<const float4*>(ml)[3];
                    l = ((l0.x + l0.y) + (l0.z + l0.w)) + ((l1.x + l1.y) + (l1.z + l1.w));
                    if (lane < 16) st_w1(ml_dst, tagw((lane & 1) ? l : m, tag));
                }
                if (ct == 224) TL(5);
            }
            {
                uint4 pf[8];
#pragma unroll
                for (int i = 0; i < 8; i++) pf[i] = lds16(sb + SM_P + t * 144 + i * 16);
                const uint32_t va = sb + SM_V + (cw >> 2) * 2048 + ((mi >> 1) * 8 + ri) * 128 + (((2 * (cw & 3) + (mi & 1)) ^ ri) * 16);
                float cA[4] = {0.f, 0.f, 0.f, 0.f}, cB[4] = {0.f, 0.f, 0.f, 0.f};
#pragma unroll
                for (int i = 0; i < 8; i++) {
                    mbar_wait(bars + (BAR_V + i) * 8);
                    const uint4 a0 = ldsm4t(va + i * 8192), a1 = ldsm4t(va + i * 8192 + 4096);
                    mma16816(cA, a0.x, a0.y, a0.z, a0.w, pf[i].x, pf[i].y);
                    mma16816(cB, a1.x, a1.y, a1.z, a1.w, pf[i].z, pf[i].w);
                }
                st_w1(o_dst, tagw(selp(cA[2] + cB[2], cA[0] + cB[0], t & 1), tag));
                if (ct == 0) TL(4);
            }
            mbar_wait(bars + BAR_SIDE * 8);
            side = misc[1];
            sd0 = ld_w1(scr + near_off(PR_SIDE, side) + oct * 8); sd1 = ld_w1(scr + near_off(PR_SIDE, side) + oct * 8 + 8);
            if (b < NWO) {
                const int ks = cw >> 1;
                const uint32_t ab = sb + SM_K + (16 * ks + (mi >> 1) * 8 + ri) * 64 + (((2 * (cw & 1) + (mi & 1)) ^ ((ri >> 1) & 3)) * 16);
                uint4 a[2 * NPRE];
                {
                    const unsigned* po = scr + near_off(PR_O + 8 * (b / 20) + cw, side);
                    uint2 sv[4];
#pragma unroll 1
                    for (int n = 0; n < SPIN_LIMIT; n++) {
#pragma unroll
                        for (int q = 0; q < 4; q++) sv[q] = ld_w2(po + 160 * q + 128);
                        if (!(bad2(sv[0], tag) | bad2(sv[1], tag) | bad2(sv[2], tag) | bad2(sv[3], tag))) break;
                    }
                    __syncwarp();
                    const float M = fmaxf(fmaxf(untag(sv[0].x), untag(sv[1].x)), fmaxf(untag(sv[2].x), untag(sv[3].x)));
                    float fq[4];
#pragma unroll
                    for (int q = 0; q < 4; q++) fq[q] = __expf(untag(sv[q].x) - M);
                    const float inv = fast_rcp((fq[0] * untag(sv[0].y) + fq[1] * untag(sv[1].y)) + (fq[2] * untag(sv[2].y) + fq[3] * untag(sv[3].y)));
#pragma unroll
                    for (int q = 0; q < 4; q++) fq[q] *= inv;
                    uint4 ov[4];
#pragma unroll
                    for (int i = 0; i < NPRE; i++) {
                        mbar_wait(bars + (BAR_WO + i) * 8);
                        if (i == NTRIG) {
#pragma unroll
                            for (int q = 0; q < 4; q++) ov[q] = ld_w4(po + 160 * q + 4 * lane);
                        }
                        a[2 * i] = ldsm4t(ab + i * 8192); a[2 * i + 1] = ldsm4t(ab + i * 8192 + 4096);
                    }
#pragma unroll 1
                    for (int n = 0; n < SPIN_LIMIT; n++) {
                        bool miss = false;
#pragma unroll
                        for (int q = 0; q < 4; q++) if (bad4(ov[q], tag)) { ov[q] = ld_w4(po + 160 * q + 4 * lane); miss = true; }
                        if (!__any_sync(FULL, miss)) break;
                    }
                    const float r0 = (fq[0] * __uint_as_float(ov[0].x) + fq[1] * __uint_as_float(ov[1].x)) + (fq[2] * __uint_as_float(ov[2].x) + fq[3] * __uint_as_float(ov[3].x));
                    const float r1 = (fq[0] * __uint_as_float(ov[0].y) + fq[1] * __uint_as_float(ov[1].y)) + (fq[2] * __uint_as_float(ov[2].y) + fq[3] * __uint_as_float(ov[3].y));
                    const float r2 = (fq[0] * __uint_as_float(ov[0].z) + fq[1] * __uint_as_float(ov[1].z)) + (fq[2] * __uint_as_float(ov[2].z) + fq[3] * __uint_as_float(ov[3].z));
                    const float r3 = (fq[0] * __uint_as_float(ov[0].w) + fq[1] * __uint_as_float(ov[1].w)) + (fq[2] * __uint_as_float(ov[2].w) + fq[3] * __uint_as_float(ov[3].w));
                    unsigned* of = reinterpret_cast<unsigned*>(smem + SM_OF) + (((lane >> 2) & 3) * 4 + 2 * (lane & 1)) * 36 +
                                   (2 * cw + (lane >> 4)) * 2 + ((lane >> 1) & 1);
                    of[0] = pack_bf(r0, r1);
                    of[36] = pack_bf(r2, r3);
                }
                bar_sync(NB_ATT, 256);
                uint4 bf[8];
#pragma unroll
                for (int i = 0; i < 8; i++) bf[i] = lds16(sb + SM_OF + (ks * 4 + t) * 144 + i * 16);
                if (ct == 0) TLD(29, __uint_as_float(bf[0].x));
                float cA[4] = {0.f, 0.f, 0.f, 0.f}, cB[4] = {0.f, 0.f, 0.f, 0.f};
#pragma unroll
                for (int i = 0; i < NPRE; i++) {
                    mma16816(cA, a[2 * i].x, a[2 * i].y, a[2 * i].z, a[2 * i].w, bf[i].x, bf[i].y);
                    mma16816(cB, a[2 * i + 1].x, a[2 * i + 1].y, a[2 * i + 1].z, a[2 * i + 1].w, bf[i].z, bf[i].w);
                }
#pragma unroll
                for (int i = NPRE; i < 8; i++) {
                    mbar_wait(bars + (BAR_WO + i) * 8);
                    const uint4 a0 = ldsm4t(ab + i * 8192), a1 = ldsm4t(ab + i * 8192 + 4096);
                    mma16816(cA, a0.x, a0.y, a0.z, a0.w, bf[i].x, bf[i].y);
                    mma16816(cB, a1.x, a1.y, a1.z, a1.w, bf[i].z, bf[i].w);
                }
                sts_p(sb + SM_HP + ((16 * (cw & 1) + g + 8 * (t & 1)) * 4 + ks) * 4, selp(cA[2] + cB[2], cA[0] + cB[0], t & 1), t < 2);
                bar_arrive(NB_HP, 288);
                if (ct == 0) TL(6);
            }
        } else {
            unsigned* const probe = scr + near_off(PR_PROBE + (b >> 2), cw & 1) + (b & 3) * 256;
            st_w1(probe + (lane >> 3) * 32 + (lane & 7), 0u);
            st_w1(probe + 128 + (lane >> 3) * 32 + (lane & 7), 0u);
            if (cw == 8 && lane == 0) misc[2] = 0u;
            wait_until(tstart, pc.tP);
            bar_sync(NB_PROBE, 64);
            unsigned v = 0;
#pragma unroll 1
            for (int i = 0; i < pc.nprobe; i++) v = ld_w1(probe + i * 32 + v);
            unsigned won = 0;
            if (lane == 0) won = (atomicExch(reinterpret_cast<unsigned*>(smem + SM_TAG) + 2, 1u + v) == 0u);
            won = __shfl_sync(FULL, won, 0);
            if (cw & 1) bar_sync(NB_TAG1, 64); else bar_sync(NB_TAG0, 64);
            tag = misc[0];
            if (pc.mode == 1) return;
            if (won) {
                const unsigned sd = cw & 1;
                if (lane == 0) {
                    misc[1] = sd;
                    mbar_arrive(bars + BAR_SIDE * 8);
                    TL(23);
                }
                if (f < NOCT) {
                    unsigned* i1 = scr + near_off(PR_D + f, sd) + 4 * lane;
#pragma unroll
                    for (int j = 0; j < 7; j++) {
                        const unsigned z = (j * 16 + (lane >> 1) >= NFFN) ? tag : 0u;
                        st_w4(i1 + 128 * j, make_uint4(z, z, z, z));
                    }
                    __threadfence();
                    __syncwarp();
                    if (lane < 16) st_w1(scr + PR_SIDE * PAIR_W + (lane >> 3) * REP_W + f * 8 + (lane & 7), (sd << 2) | tag);
                    if (lane == 0) { mbar_arrive(bars + BAR_CLR * 8); TL(30); }
                }
            }
            mbar_wait(bars + (BAR_V + 7) * 8);
            mbar_wait(bars + BAR_SIDE * 8);
            side = misc[1];
            sd0 = ld_w1(scr + near_off(PR_SIDE, side) + oct * 8); sd1 = ld_w1(scr + near_off(PR_SIDE, side) + oct * 8 + 8);
        }
        if (f >= NFFN) return;

        const unsigned* const sd_src = scr + near_off(PR_SIDE, side) + oct * 8;
        const unsigned* const h_src0 = pin(scr + near_off(PR_H + 4 * (b & 1), side) + 2 * ct);
        const unsigned* const h_src1 = pin(scr + near_off(PR_H + 4 * (b & 1) + 1, side) + 2 * ct);
        const unsigned* const h_src2 = pin(scr + near_off(PR_H + 4 * (b & 1) + 2, side) + 2 * ct);
        const unsigned* const h_src3 = pin(scr + near_off(PR_H + 4 * (b & 1) + 3, side) + 2 * ct);
#pragma unroll 1
        for (int n = 0; n < SPIN_LIMIT; n++) {
            if (!__any_sync(FULL, (sd0 & sd1 & tag) == 0)) break;
            __nanosleep(100);
            sd0 = ld_w1(sd_src); sd1 = ld_w1(sd_src + 8);
        }
        unsigned* const d_a = pin(scr + near_off(PR_D + oct, sd0 >> 2) + f * 8 + g);
        unsigned* const d_b = pin(scr + near_off(PR_D + oct + 1, sd1 >> 2) + f * 8 + g);
        uint32_t dp_w = sb + SM_DP + ((g + 8 * t) * 12 + cw) * 4;
        uint32_t st_w = sb + SM_DP + ((32 + lane) * 12 + cw) * 4;
        uint32_t w2_r = sb + SM_W2 + ((mi >> 1) * 8 + ri) * ROW_PITCH + cw * 128 + (mi & 1) * 16;
        uint32_t w1_r = sb + SM_W1 + (64 * cw + (mi >> 1) * 8 + ri) * 32 + (((mi & 1) ^ (ri >> 2)) * 16);
        uint32_t w1_bar = bars + (BAR_W1 + (cw >> 1)) * 8;
        asm volatile("" : "+r"(dp_w), "+r"(st_w), "+r"(w2_r), "+r"(w1_r), "+r"(w1_bar));
        wait_until(tstart, pc.tH);
        uint2 h0 = ld_w2(h_src0), h1 = ld_w2(h_src1), h2 = ld_w2(h_src2), h3 = ld_w2(h_src3);
        uint4 a[4];
        bool w1_in = false;
#pragma unroll 1
        for (int n = 0; n < SPIN_LIMIT; n++) {
            if (!w1_in && mbar_test(w1_bar)) {
                w1_in = true;
#pragma unroll
                for (int s = 0; s < 4; s++) a[s] = ldsm4t(w1_r + s * 512);
            }
            bool miss = false;
            if (bad2(h0, tag)) { h0 = ld_w2(h_src0); miss = true; }
            if (bad2(h1, tag)) { h1 = ld_w2(h_src1); miss = true; }
            if (bad2(h2, tag)) { h2 = ld_w2(h_src2); miss = true; }
            if (bad2(h3, tag)) { h3 = ld_w2(h_src3); miss = true; }
            if (!__any_sync(FULL, miss)) break;
        }
        const unsigned att = pack_bf((__uint_as_float(h0.x) + __uint_as_float(h1.x)) + (__uint_as_float(h2.x) + __uint_as_float(h3.x)),
                                     (__uint_as_float(h0.y) + __uint_as_float(h1.y)) + (__uint_as_float(h2.y) + __uint_as_float(h3.y)));
        const unsigned hpair = pack_bf(bf_lo(xpair) + bf_lo(att), bf_hi(xpair) + bf_hi(att));
        if (ct == 0) TL(8);
        unsigned hf[8];
#pragma unroll
        for (int s = 0; s < 8; s++) hf[s] = __shfl_sync(FULL, hpair, 4 * s + t);
        {
            float sA[4] = {0.f, 0.f, 0.f, 0.f}, sB[4] = {0.f, 0.f, 0.f, 0.f};
#pragma unroll
            for (int s = 0; s < 4; s += 2) {
                mma16816(sA, hf[2 * s], 0x3F803F80u, hf[2 * s + 1], 0x3F803F80u, hf[2 * s], hf[2 * s + 1]);
                mma16816(sB, hf[2 * s + 2], 0x3F803F80u, hf[2 * s + 3], 0x3F803F80u, hf[2 * s + 2], hf[2 * s + 3]);
            }
            if (!w1_in) {
                mbar_wait(w1_bar);
#pragma unroll
                for (int s = 0; s < 4; s++) a[s] = ldsm4t(w1_r + s * 512);
            }
            float dA[4] = {0.f, 0.f, 0.f, 0.f}, dB[4] = {0.f, 0.f, 0.f, 0.f};
#pragma unroll
            for (int s = 0; s < 8; s++) hf[s] = (g < 4) ? hf[s] : 0x3F803F80u;
#pragma unroll
            for (int s = 0; s < 4; s += 2) {
                mma16816(dA, a[s].x, a[s].y, a[s].z, a[s].w, hf[2 * s], hf[2 * s + 1]);
                mma16816(dB, a[s + 1].x, a[s + 1].y, a[s + 1].z, a[s + 1].w, hf[2 * s + 2], hf[2 * s + 3]);
            }
            sts_p(st_w, selp(sA[2] + sB[2], sA[0] + sB[0], lane), lane < 2);
            sts_p(dp_w, selp(dA[2] + dB[2], dA[0] + dB[0], t & 1), 1u);
        }
        if (ct == 0) TL(7);
        bar_arrive(NB_FPART, 352);
        uint4 w[4];
        mbar_wait(bars + BAR_W2 * 8);
#pragma unroll
        for (int j = 0; j < 4; j++) w[j] = ldsm4t(w2_r + j * 32);
        bar_sync(NB_H1, 352);
        unsigned b0, b1;
        asm volatile("ld.shared.u32 %0, [%1];" : "=r"(b0) : "r"(sb + SM_H1 + 4 * t) : "memory");
        asm volatile("ld.shared.u32 %0, [%1];" : "=r"(b1) : "r"(sb + SM_H1 + 16 + 4 * t) : "memory");
        float y[4][4];
#pragma unroll
        for (int j = 0; j < 4; j++) {
            y[j][0] = y[j][1] = y[j][2] = y[j][3] = 0.f;
            mma16816(y[j], w[j].x, w[j].y, w[j].z, w[j].w, b0, b1);
        }
        st_w1(d_a, tagw(sel4(y[0][0], y[1][0], y[2][0], y[3][0], t), tag));
        st_w1(d_b, tagw(sel4(y[0][2], y[1][2], y[2][2], y[3][2], t), tag));
        if (ct == 0) TL(9);
        if (f < NOCT) bar_arrive(NB_DSENT, 352);
    } else if (warp == 1) {
        const unsigned t0 = tstart + (unsigned)((h & 7) * pc.stag);
        if (lane == 0) {
            TLV(0, tstart);
#pragma unroll
            for (int i = 0; i < BAR_KFREE; i++) mbar_init(bars + i * 8, 1);
            mbar_init(bars + BAR_KFREE * 8, 8);
            asm volatile("fence.mbarrier_init.release.cluster;" ::: "memory");
            asm volatile("prefetch.tensormap [%0];" :: "l"(&map_v) : "memory");
            asm volatile("prefetch.tensormap [%0];" :: "l"(&map_w1) : "memory");
            asm volatile("prefetch.tensormap [%0];" :: "l"(&map_wo) : "memory");
        }
        bar_arrive(NB_XN, N_XN);
        if (lane == 0) {
            int tt = pc.tK;
            const char* ks = reinterpret_cast<const char*>(kc) + (size_t)h * 1048576 + 786432 + c * 65536;
#pragma unroll 1
            for (int ii = 0; ii < 16; ii++) {
                const int i = ii;
                wait_until(t0, tt); tt += pc.dKV;
                mbar_expect_tx(bars + (BAR_K + i) * 8, 4096);
                bulk_g2s(sb + SM_K + i * 4096, ks + i * 4096, 4096, bars + (BAR_K + i) * 8);
            }
#pragma unroll 1
            for (int ii = 0; ii < 16; ii++) {
                const int i = ii;
                wait_until(t0, tt); tt += pc.dKV;
                if (!(i & 1)) mbar_expect_tx(bars + (BAR_V + (i >> 1)) * 8, 8192);
                tma3d(sb + SM_V + i * 4096, &map_v, 0, h * 4096 + 3072 + 256 * c + 16 * i, 0, bars + (BAR_V + (i >> 1)) * 8);
            }
#pragma unroll 1
            for (int j = 0; j < 5; j++) {
                if (j == pc.npre) {
                    if (b < NWO) {
                        const int c0 = 32 * (b % 20), r0 = 1024 * (b / 20);
                        if (pc.mode != 1) mbar_wait(bars + BAR_KFREE * 8);
#pragma unroll 1
                        for (int i = 0; i < 16; i++) {
                            wait_until(t0, tt); tt += pc.dWO;
                            if (!(i & 1)) mbar_expect_tx(bars + (BAR_WO + (i >> 1)) * 8, 8192);
                            tma2d(sb + SM_K + i * 4096, &map_wo, c0, r0 + 64 * i, bars + (BAR_WO + (i >> 1)) * 8);
                        }
                    } else {
                        tt += 16 * pc.dWO - pc.early;
                    }
                    tt += pc.gap;
                }
                if (f < NFFN) {
                    wait_until(t0, tt);
                    mbar_expect_tx(bars + (BAR_W1 + j) * 8, 4096);
                    tma2d(sb + SM_W1 + j * 4096, &map_w1, 16 * f, 128 * j, bars + (BAR_W1 + j) * 8);
                }
                tt += pc.dW1;
            }
            if (f < NFFN) {
                const char* w2s = reinterpret_cast<const char*>(w2) + (size_t)f * 16 * 1280;
                mbar_expect_tx(bars + BAR_W2 * 8, 16 * 1280);
#pragma unroll 1
                for (int j = 0; j < 4; j++) {
                    wait_until(t0, tt); tt += pc.dW2;
#pragma unroll
                    for (int i = 0; i < 4; i++) {
                        const int r = j * 4 + i;
                        bulk_g2s(sb + SM_W2 + r * ROW_PITCH, w2s + r * 1280, 1280, bars + BAR_W2 * 8);
                    }
                }
                TL(10);
            }
            if (pc.mode == 1) {
                for (int i = 0; i < BAR_SIDE; i++)
                    if (i < BAR_V + 8 || (i >= BAR_WO && (i < BAR_W1 ? b < NWO : f < NFFN))) mbar_wait(bars + i * 8);
            }
        }
    } else {
        const int col = 8 * f + 4 * (lane & 1) + (lane & 2) + ((lane >> 2) & 1);
        float xcol = 0.f;
        if (f < NOCT) xcol = __bfloat162float(x[col]);
        {
            float s = 0.f;
#pragma unroll
            for (int j = 0; j < 5; j++) s += (bf_lo(xr[j].x) + bf_hi(xr[j].x)) + (bf_lo(xr[j].y) + bf_hi(xr[j].y));
#pragma unroll
            for (int o = 16; o; o >>= 1) s += __shfl_xor_sync(FULL, s, o);
            const float mean = s * (1.0f / 640.0f);
            float v = 0.f;
#pragma unroll
            for (int j = 0; j < 5; j++) {
                float d0 = bf_lo(xr[j].x) - mean, d1 = bf_hi(xr[j].x) - mean, d2 = bf_lo(xr[j].y) - mean, d3 = bf_hi(xr[j].y) - mean;
                v += (d0 * d0 + d1 * d1) + (d2 * d2 + d3 * d3);
            }
#pragma unroll
            for (int o = 16; o; o >>= 1) v += __shfl_xor_sync(FULL, v, o);
            const float mb = bfr(mean);
            const float rb = __frcp_rn(bfr(__fsqrt_rn(bfr(bfr(v * (1.0f / 640.0f)) + 1e-5f))));
            float4* xn = reinterpret_cast<float4*>(smem + SM_XN);
#pragma unroll
            for (int j = 0; j < 5; j++) {
                float4 o;
                o.x = bfr(bfr(bf_lo(xr[j].x) - mb) * rb); o.y = bfr(bfr(bf_hi(xr[j].x) - mb) * rb);
                o.z = bfr(bfr(bf_lo(xr[j].y) - mb) * rb); o.w = bfr(bfr(bf_hi(xr[j].y) - mb) * rb);
                xn[j * 32 + lane] = o;
            }
        }
        const unsigned tag = 1u + (epoch & 1u);
        if (lane == 0) misc[0] = tag;
        if (lane == 0) TL(22);
        bar_sync(NB_XN, N_XN);
        bar_arrive(NB_TAG0, 64);
        bar_arrive(NB_TAG1, 64);
        unsigned* const a_dst = scr + (PR_A + (h >> 1)) * PAIR_W + (b & 7) * 128 + 4 * lane;
        unsigned* const h_dst = pin(scr + (PR_H + b / 20) * PAIR_W + 32 * (b % 20) + lane);
        st_w4(a_dst, make_uint4(0u, 0u, 0u, 0u));
        st_w4(a_dst + REP_W, make_uint4(0u, 0u, 0u, 0u));
        if (b < NWO) { st_w1(h_dst, 0u); st_w1(h_dst + REP_W, 0u); st_w1(h_dst + 4 * PAIR_W, 0u); st_w1(h_dst + 4 * PAIR_W + REP_W, 0u); }
        bar_sync(NB_QPART, 288);
        {
            const float4* qp = reinterpret_cast<const float4*>(smem + SM_QPART) + lane;
            float4 s = qp[0];
            if (lane == 0) TLD(1, s.x);
#pragma unroll
            for (int w = 1; w < 8; w++) { const float4 u = qp[w * 32]; s.x += u.x; s.y += u.y; s.z += u.z; s.w += u.w; }
            const uint4 mine = make_uint4(tagw(s.x, tag), tagw(s.y, tag), tagw(s.z, tag), tagw(s.w, tag));
            st_w4(a_dst, mine);
            st_w4(a_dst + REP_W, mine);
            if (pc.mode == 1) return;
            mbar_wait(bars + BAR_SIDE * 8);
            const unsigned* pa = scr + near_off(PR_A + (h >> 1), misc[1]) + (h & 1) * 512 + 4 * lane;
            uint4 v[4];
#pragma unroll 1
            for (int n = 0; n < SPIN_LIMIT; n++) {
#pragma unroll
                for (int cc = 0; cc < 4; cc++) v[cc] = (cc == c) ? mine : ld_w4(pa + cc * 128);
                if (!__any_sync(FULL, bad4(v[0], tag) | bad4(v[1], tag) | bad4(v[2], tag) | bad4(v[3], tag))) break;
                __nanosleep(pc.slp);
            }
            const float q0 = ((untag(v[0].x) + untag(v[1].x)) + untag(v[2].x)) + untag(v[3].x);
            const float q1 = ((untag(v[0].y) + untag(v[1].y)) + untag(v[2].y)) + untag(v[3].y);
            const float q2 = ((untag(v[0].z) + untag(v[1].z)) + untag(v[2].z)) + untag(v[3].z);
            const float q3 = ((untag(v[0].w) + untag(v[1].w)) + untag(v[2].w)) + untag(v[3].w);
            reinterpret_cast<uint2*>(smem + SM_QS)[lane] = make_uint2(pack_bf(q0, q1), pack_bf(q2, q3));
        }
        bar_arrive(NB_Q, 288);
        if (lane == 0) TL(2);
        const unsigned side = misc[1];
        const unsigned* const d_src = pin(scr + near_off(PR_D + f, side) + 4 * lane);
        const unsigned* const hb0 = pin(scr + near_off(PR_H + 4 * (b & 1) + (lane >> 3), side) + col);
        __nv_bfloat16* const o_dst = pin(out + col);
        int lane_p = lane, dly_d = pc.dlyD;
        uint32_t hp_r = sb + SM_HP + lane * 16;
        asm volatile("" : "+r"(lane_p), "+r"(dly_d), "+r"(hp_r));
        if (b < NWO) {
            bar_sync(NB_HP, 288);
            const uint4 u0 = lds16(hp_r);
            const unsigned hw = tagw((__uint_as_float(u0.x) + __uint_as_float(u0.y)) + (__uint_as_float(u0.z) + __uint_as_float(u0.w)), tag);
            st_w1(h_dst, hw); st_w1(h_dst + REP_W, hw); st_w1(h_dst + 4 * PAIR_W, hw); st_w1(h_dst + 4 * PAIR_W + REP_W, hw);
            if (lane_p == 0) TL(12);
        }
        if (f >= NFFN) return;
        {
            uint32_t dp_r = sb + SM_DP + lane * 48, st_r = sb + SM_DP + (32 + (lane & 1)) * 48, h1_w = sb + SM_H1 + 2 * lane;
            asm volatile("" : "+r"(dp_r), "+r"(st_r), "+r"(h1_w));
            bar_sync(NB_FPART, 352);
            const uint4 s0 = lds16(st_r), s1 = lds16(st_r + 16), u0 = lds16(dp_r), u1 = lds16(dp_r + 16);
            float s2x, s2y, u2x, u2y;
            asm volatile("ld.shared.v2.f32 {%0,%1}, [%2];" : "=f"(s2x), "=f"(s2y) : "r"(st_r + 32) : "memory");
            asm volatile("ld.shared.v2.f32 {%0,%1}, [%2];" : "=f"(u2x), "=f"(u2y) : "r"(dp_r + 32) : "memory");
            if (lane_p == 0) TLD(21, u2x);
            const float st = (((__uint_as_float(s0.x) + __uint_as_float(s0.y)) + (__uint_as_float(s0.z) + __uint_as_float(s0.w))) +
                              ((__uint_as_float(s1.x) + __uint_as_float(s1.y)) + (__uint_as_float(s1.z) + __uint_as_float(s1.w))) + (s2x + s2y)) * (1.0f / 640.0f);
            const float tot = ((__uint_as_float(u0.x) + __uint_as_float(u0.y)) + (__uint_as_float(u0.z) + __uint_as_float(u0.w))) +
                              ((__uint_as_float(u1.x) + __uint_as_float(u1.y)) + (__uint_as_float(u1.z) + __uint_as_float(u1.w))) + (u2x + u2y);
            const float so = __shfl_xor_sync(FULL, st, 1);
            const float cs = __shfl_xor_sync(FULL, tot, 16);
            const float mean = selp(st, so, lane_p & 1), msq = selp(so, st, lane_p & 1);
            const float var = fmaxf(fmaf(-mean, mean, msq), 0.f);
            const float rinv = fast_rcp(bfr(fast_sqrt(bfr(bfr(var) + 1e-5f))));
            const float z = fmaxf(fmaf(-bfr(mean), cs, tot) * rinv, 0.f);
            if (lane_p < 16) asm volatile("st.shared.u16 [%0], %1;" :: "r"(h1_w), "h"((unsigned short)pack_bf(z, 0.f)) : "memory");
            bar_arrive(NB_H1, 352);
        }
        if (f >= NOCT) return;
        mbar_wait(bars + BAR_CLR * 8);
        unsigned ha = ld_w1(hb0);
        bar_sync(NB_DSENT, 352);
        spin_cycles(dly_d);
        {
            uint4 v[7];
#pragma unroll
            for (int j = 0; j < 7; j++) v[j] = ld_w4(d_src + 128 * j);
#pragma unroll 1
            for (int n = 0; n < SPIN_LIMIT; n++) {
                if (!__any_sync(FULL, (ha & tag) == 0)) break;
                ha = ld_w1(hb0);
            }
            float hs = __uint_as_float(ha);
            hs += __shfl_xor_sync(FULL, hs, 8);
            hs += __shfl_xor_sync(FULL, hs, 16);
            const float base = bfr(xcol + bfr(hs));
            float r = 0.f;
#pragma unroll 1
            for (int n = 0; n < SPIN_LIMIT; n++) {
                float t0 = ((__uint_as_float(v[0].x) + __uint_as_float(v[1].x)) + (__uint_as_float(v[2].x) + __uint_as_float(v[3].x))) +
                           ((__uint_as_float(v[4].x) + __uint_as_float(v[5].x)) + __uint_as_float(v[6].x));
                float t1 = ((__uint_as_float(v[0].y) + __uint_as_float(v[1].y)) + (__uint_as_float(v[2].y) + __uint_as_float(v[3].y))) +
                           ((__uint_as_float(v[4].y) + __uint_as_float(v[5].y)) + __uint_as_float(v[6].y));
                float t2 = ((__uint_as_float(v[0].z) + __uint_as_float(v[1].z)) + (__uint_as_float(v[2].z) + __uint_as_float(v[3].z))) +
                           ((__uint_as_float(v[4].z) + __uint_as_float(v[5].z)) + __uint_as_float(v[6].z));
                float t3 = ((__uint_as_float(v[0].w) + __uint_as_float(v[1].w)) + (__uint_as_float(v[2].w) + __uint_as_float(v[3].w))) +
                           ((__uint_as_float(v[4].w) + __uint_as_float(v[5].w)) + __uint_as_float(v[6].w));
                asm volatile("" : "+f"(t0), "+f"(t1), "+f"(t2), "+f"(t3));
                bool miss = false;
#pragma unroll
                for (int j = 0; j < 7; j++)
                    if (bad4(v[j], tag)) { v[j] = ld_w4(d_src + 128 * j); miss = true; }
                const bool again = __any_sync(FULL, miss);
                r = octet_reduce(t0, t1, t2, t3, lane_p);
                if (!again) break;
            }
            if (lane_p < 8) asm volatile("st.global.u16 [%0], %1;" :: "l"(o_dst), "h"((unsigned short)pack_bf(base + bfr(r), 0.f)) : "memory");
            if (lane_p == 0) TL(13);
        }
        if (f == 0 && lane == 0) st_w1(scr + PR_EPOCH * PAIR_W, epoch + 1u);
    }
}

Pace g_pace = {1150, 165, 103, 139, 174, 20, 200, 250, 4, 8, 600, 0, 0, 0, 400, 50, 9500};
unsigned* g_scr_base = nullptr;
int g_w1_promo = 2;
int g_v_promo = 2;
int g_wo_promo = 2;

}

typedef CUresult (*EncodeTiledFn)(CUtensorMap*, CUtensorMapDataType, cuuint32_t, void*, const cuuint64_t*, const cuuint64_t*,
                                  const cuuint32_t*, const cuuint32_t*, CUtensorMapInterleave, CUtensorMapSwizzle,
                                  CUtensorMapL2promotion, CUtensorMapFloatOOBfill);

extern "C" void kernel_launch(void* const* d_in, const int* in_sizes, int n_in, void* d_out, int out_size) {
    (void)in_sizes; (void)n_in; (void)out_size;
    static EncodeTiledFn encode = nullptr;
    if (!encode) {
        cudaFuncSetAttribute(fk::fused_decode_kernel, cudaFuncAttributeMaxDynamicSharedMemorySize, fk::SMEM_BYTES);
        void* fn = nullptr;
        cudaDriverEntryPointQueryResult qres;
        cudaGetDriverEntryPoint("cuTensorMapEncodeTiled", &fn, cudaEnableDefault, &qres);
        encode = (EncodeTiledFn)fn;
        void* sp = nullptr;
        cudaGetSymbolAddress(&sp, fk::g_scr);
        fk::g_scr_base = (unsigned*)(((uintptr_t)sp + (2u << 20) - 1) & ~(uintptr_t)((2u << 20) - 1));
    }
    CUtensorMap map_v, map_w1, map_wo;
    {
        const cuuint64_t dims[2] = {640, 4096}, strides[1] = {1280};
        const cuuint32_t box[2] = {32, 64}, es[2] = {1, 1};
        encode(&map_wo, CU_TENSOR_MAP_DATA_TYPE_BFLOAT16, 2, d_in[4], dims, strides, box, es, CU_TENSOR_MAP_INTERLEAVE_NONE,
               CU_TENSOR_MAP_SWIZZLE_64B, (CUtensorMapL2promotion)fk::g_wo_promo, CU_TENSOR_MAP_FLOAT_OOB_FILL_NONE);
    }
    {
        const cuuint64_t dims[3] = {64, 32 * 4096, 2}, strides[2] = {256, 128};
        const cuuint32_t box[3] = {64, 16, 2}, es[3] = {1, 1, 1};
        encode(&map_v, CU_TENSOR_MAP_DATA_TYPE_BFLOAT16, 3, d_in[2], dims, strides, box, es, CU_TENSOR_MAP_INTERLEAVE_NONE,
               CU_TENSOR_MAP_SWIZZLE_128B, (CUtensorMapL2promotion)fk::g_v_promo, CU_TENSOR_MAP_FLOAT_OOB_FILL_NONE);
    }
    {
        const cuuint64_t dims[2] = {1728, 640}, strides[1] = {3456};
        const cuuint32_t box[2] = {16, 128}, es[2] = {1, 1};
        encode(&map_w1, CU_TENSOR_MAP_DATA_TYPE_BFLOAT16, 2, d_in[6], dims, strides, box, es, CU_TENSOR_MAP_INTERLEAVE_NONE,
               CU_TENSOR_MAP_SWIZZLE_32B, (CUtensorMapL2promotion)fk::g_w1_promo, CU_TENSOR_MAP_FLOAT_OOB_FILL_NONE);
    }
    fk::fused_decode_kernel<<<fk::NCTA, fk::NTHREADS, fk::SMEM_BYTES>>>(
        (const __nv_bfloat16*)d_in[0], (const __nv_bfloat16*)d_in[3], (const __nv_bfloat16*)d_in[1],
        (const __nv_bfloat16*)d_in[7], (__nv_bfloat16*)d_out, fk::g_scr_base, fk::g_pace, map_v, map_w1, map_wo);
}
```

```cpp
#include <cuda_runtime.h>
#include <cuda.h>
#include <cuda_bf16.h>
#include <stdint.h>
#include <stdlib.h>

namespace fk {

constexpr int NCTA = 128;
constexpr int NFFN = 108;
constexpr int NOCT = 80;
constexpr int NWO = 80;
constexpr int NTHREADS = 384;

constexpr int ROW_PITCH = 1296;
constexpr int SM_K = 0;
constexpr int SM_V = 65536;
constexpr int SM_W1 = 131072;
constexpr int SM_W2 = SM_W1 + 640 * 32;
constexpr int SM_QPART = SM_W2 + 16 * ROW_PITCH;
constexpr int SM_P = SM_QPART + 4096;
constexpr int SM_XN = SM_P + 576;
constexpr int SM_ML = SM_XN + 2560;
constexpr int SM_QS = SM_ML + 64;
constexpr int SM_HP = SM_QS + 256;
constexpr int SM_DP = SM_HP + 32 * 48;
constexpr int SM_H1 = SM_DP + 34 * 48;
constexpr int SM_OF = SM_H1 + 32;
constexpr int SM_TAG = SM_OF + 16 * 144;
constexpr int SM_BAR = SM_TAG + 32;
constexpr int BAR_K = 0, BAR_V = 16, BAR_WO = 32, BAR_W1 = 40, BAR_W2 = 45, BAR_SIDE = 46, BAR_CLR = 47, BAR_KFREE = 48, BAR_O = 49, NBAR = 50;
constexpr int SMEM_BYTES = SM_BAR + NBAR * 8;

constexpr int SPIN_LIMIT = 1 << 17;
#define NPRE 7

struct Pace {
    int tK;
    int dKV;
    int dWO;
    int dW1;
    int dW2;
    int stag;
    int gap;
    int dlyD;
    int dlyO;
    int nprobe;
    int tP;
    int mode;
};
#define PACE_DEFAULT {1120, 165, 105, 139, 100, 20, 200, 250, 600, 8, 600, 0}

__device__ __align__(4096) unsigned g_scr[1 << 20];
constexpr int PAIR_W = 2048, REP_W = 1024;
constexpr int PR_D = 0;
constexpr int PR_H = 172;
constexpr int PR_O = 88;
constexpr int PR_A = 120;
constexpr int PR_SIDE = 136;
constexpr int PR_PROBE = 137;
constexpr int PR_EPOCH = 169;
constexpr int PR_TL = 170;
__device__ __forceinline__ int near_off(int pair, unsigned side) {
    return pair * PAIR_W + (int)((side ^ __popc((2 * pair) & 0xb3)) & 1u) * REP_W;
}
#define TL(i) do {} while (0)
#define TLD(i, v) do {} while (0)
#define TLV(i, v) do {} while (0)

__device__ __forceinline__ unsigned gtime32() {
    unsigned long long t; asm volatile("mov.u64 %0, %globaltimer;" : "=l"(t) :: "memory"); return (unsigned)t;
}
__device__ __forceinline__ uint32_t smem_u32(const void* p) { return (uint32_t)__cvta_generic_to_shared(p); }
__device__ __forceinline__ void mbar_init(uint32_t bar, uint32_t cnt) {
    asm volatile("mbarrier.init.shared::cta.b64 [%0], %1;" :: "r"(bar), "r"(cnt) : "memory");
}
__device__ __forceinline__ void mbar_expect_tx(uint32_t bar, uint32_t bytes) {
    asm volatile("mbarrier.arrive.expect_tx.shared::cta.b64 _, [%0], %1;" :: "r"(bar), "r"(bytes) : "memory");
}
__device__ __forceinline__ void mbar_arrive(uint32_t bar) {
    asm volatile("mbarrier.arrive.shared::cta.b64 _, [%0];" :: "r"(bar) : "memory");
}
__device__ __forceinline__ void mbar_arrive_p(uint32_t bar, unsigned p) {
    asm volatile("{\n.reg .pred p;\nsetp.ne.u32 p, %1, 0;\n@p mbarrier.arrive.shared::cta.b64 _, [%0];\n}" :: "r"(bar), "r"(p) : "memory");
}
__device__ __forceinline__ bool mbar_test(uint32_t bar) {
    uint32_t ok;
    asm volatile("{\n.reg .pred p;\nmbarrier.test_wait.parity.shared::cta.b64 p, [%1], 0;\nselp.u32 %0, 1, 0, p;\n}"
                 : "=r"(ok) : "r"(bar) : "memory");
    return ok != 0;
}
__device__ __forceinline__ bool mbar_try(uint32_t bar) {
    uint32_t ok;
    asm volatile("{\n.reg .pred p;\nmbarrier.try_wait.parity.shared::cta.b64 p, [%1], 0;\nselp.u32 %0, 1, 0, p;\n}"
                 : "=r"(ok) : "r"(bar) : "memory");
    return ok != 0;
}
__device__ __forceinline__ void mbar_wait(uint32_t bar, int lim = SPIN_LIMIT) {
#pragma unroll 1
    for (int n = 0; n < lim; n++) if (mbar_try(bar)) break;
}
__device__ __forceinline__ uint64_t stream_policy() {
    uint64_t p; asm volatile("createpolicy.fractional.L2::evict_first.b64 %0, 1.0;" : "=l"(p)); return p;
}
__device__ __forceinline__ void bulk_g2s(uint32_t dst, const void* src, uint32_t bytes, uint32_t bar, uint64_t pol) {
    asm volatile("cp.async.bulk.shared::cluster.global.mbarrier::complete_tx::bytes.L2::cache_hint [%0], [%1], %2, [%3], %4;"
                 :: "r"(dst), "l"(src), "r"(bytes), "r"(bar), "l"(pol) : "memory");
}
__device__ __forceinline__ void tma3d(uint32_t dst, const CUtensorMap* map, int c0, int c1, int c2, uint32_t bar, uint64_t pol) {
    asm volatile("cp.async.bulk.tensor.3d.shared::cluster.global.mbarrier::complete_tx::bytes.L2::cache_hint [%0], [%1, {%3, %4, %5}], [%2], %6;"
                 :: "r"(dst), "l"(map), "r"(bar), "r"(c0), "r"(c1), "r"(c2), "l"(pol) : "memory");
}
__device__ __forceinline__ void tma2d(uint32_t dst, const CUtensorMap* map, int c0, int c1, uint32_t bar, uint64_t pol) {
    asm volatile("cp.async.bulk.tensor.2d.shared::cluster.global.mbarrier::complete_tx::bytes.L2::cache_hint [%0], [%1, {%3, %4}], [%2], %5;"
                 :: "r"(dst), "l"(map), "r"(bar), "r"(c0), "r"(c1), "l"(pol) : "memory");
}
__device__ __forceinline__ unsigned tagw(float v, unsigned tag) { return (__float_as_uint(v) & ~3u) | tag; }
__device__ __forceinline__ float untag(unsigned w) { return __uint_as_float(w & ~3u); }
__device__ __forceinline__ void st_w1(unsigned* p, unsigned a) {
    asm volatile("st.relaxed.gpu.global.u32 [%0], %1;" :: "l"(p), "r"(a) : "memory");
}
__device__ __forceinline__ void st_w1_p(unsigned* a, unsigned v, unsigned p) {
    asm volatile("{\n.reg .pred p;\nsetp.ne.u32 p, %2, 0;\n@p st.relaxed.gpu.global.u32 [%0], %1;\n}" :: "l"(a), "r"(v), "r"(p) : "memory");
}
__device__ __forceinline__ void st_w4(unsigned* p, uint4 v) {
    asm volatile("st.relaxed.gpu.global.v4.u32 [%0], {%1,%2,%3,%4};" :: "l"(p), "r"(v.x), "r"(v.y), "r"(v.z), "r"(v.w) : "memory");
}
__device__ __forceinline__ unsigned ld_w1(const unsigned* p) {
    unsigned v;
    asm volatile("ld.relaxed.gpu.global.u32 %0, [%1];" : "=r"(v) : "l"(p) : "memory");
    return v;
}
__device__ __forceinline__ uint4 ld_w4(const unsigned* p) {
    uint4 v;
    asm volatile("ld.relaxed.gpu.global.v4.u32 {%0,%1,%2,%3}, [%4];" : "=r"(v.x), "=r"(v.y), "=r"(v.z), "=r"(v.w) : "l"(p) : "memory");
    return v;
}
__device__ __forceinline__ uint2 ld_w2(const unsigned* p) {
    uint2 v;
    asm volatile("ld.relaxed.gpu.global.v2.u32 {%0,%1}, [%2];" : "=r"(v.x), "=r"(v.y) : "l"(p) : "memory");
    return v;
}
__device__ __forceinline__ bool bad2(uint2 v, unsigned tag) { return (v.x & v.y & tag) == 0; }
__device__ __forceinline__ bool bad4(uint4 v, unsigned tag) { return ((v.x & v.y & v.z) & v.w & tag) == 0; }

__device__ __forceinline__ void bar_sync(int id, int n) { __syncwarp(); asm volatile("bar.sync %0, %1;" :: "r"(id), "r"(n) : "memory"); }
__device__ __forceinline__ void bar_arrive(int id, int n) { __syncwarp(); asm volatile("bar.arrive %0, %1;" :: "r"(id), "r"(n) : "memory"); }
template <int ID, int N> __device__ __forceinline__ void bar_sync_p(unsigned p) {
    __syncwarp();
    asm volatile("{\n.reg .pred p;\nsetp.ne.u32 p, %0, 0;\n@p bar.sync %1, %2;\n}" :: "r"(p), "n"(ID), "n"(N) : "memory");
}
template <int ID, int N> __device__ __forceinline__ void bar_arrive_p(unsigned p) {
    __syncwarp();
    asm volatile("{\n.reg .pred p;\nsetp.ne.u32 p, %0, 0;\n@p bar.arrive %1, %2;\n}" :: "r"(p), "n"(ID), "n"(N) : "memory");
}
__device__ __forceinline__ void sts_p(uint32_t a, float v, unsigned p) {
    asm volatile("{\n.reg .pred p;\nsetp.ne.u32 p, %2, 0;\n@p st.shared.f32 [%0], %1;\n}" :: "r"(a), "f"(v), "r"(p) : "memory");
}
__device__ __forceinline__ float bf_lo(unsigned u) { return __uint_as_float(u << 16); }
__device__ __forceinline__ float bf_hi(unsigned u) { return __uint_as_float(u & 0xffff0000u); }
__device__ __forceinline__ unsigned pack_bf(float lo, float hi) {
    unsigned r; asm("cvt.rn.bf16x2.f32 %0, %1, %2;" : "=r"(r) : "f"(hi), "f"(lo)); return r;
}
__device__ __forceinline__ float bfr(float v) { return __uint_as_float(pack_bf(0.f, v)); }
__device__ __forceinline__ float selp(float a, float b, unsigned c) {
    float r; asm("{\n.reg .pred p;\nsetp.ne.u32 p, %3, 0;\nselp.f32 %0, %1, %2, p;\n}" : "=f"(r) : "f"(a), "f"(b), "r"(c)); return r;
}
__device__ __forceinline__ float sel4(float a0, float a1, float a2, float a3, int t) {
    return selp(selp(a3, a2, t & 1), selp(a1, a0, t & 1), t & 2);
}
__device__ __forceinline__ float fast_sqrt(float v) { float r; asm("sqrt.approx.ftz.f32 %0, %1;" : "=f"(r) : "f"(v)); return r; }
__device__ __forceinline__ float fast_rcp(float v) { float r; asm("rcp.approx.ftz.f32 %0, %1;" : "=f"(r) : "f"(v)); return r; }
template <class T> __device__ __forceinline__ T* pin(T* p) { asm volatile("" : "+l"(p)); return p; }
__device__ __forceinline__ void mma16816(float (&c)[4], unsigned a0, unsigned a1, unsigned a2, unsigned a3,
                                         unsigned b0, unsigned b1) {
    asm volatile("mma.sync.aligned.m16n8k16.row.col.f32.bf16.bf16.f32 {%0,%1,%2,%3}, {%4,%5,%6,%7}, {%8,%9}, {%0,%1,%2,%3};"
                 : "+f"(c[0]), "+f"(c[1]), "+f"(c[2]), "+f"(c[3])
                 : "r"(a0), "r"(a1), "r"(a2), "r"(a3), "r"(b0), "r"(b1));
}
__device__ __forceinline__ uint4 ldsm4t(uint32_t addr) {
    uint4 r;
    asm volatile("ldmatrix.sync.aligned.m8n8.x4.trans.shared.b16 {%0,%1,%2,%3}, [%4];"
                 : "=r"(r.x), "=r"(r.y), "=r"(r.z), "=r"(r.w) : "r"(addr) : "memory");
    return r;
}
__device__ __forceinline__ uint4 lds16(uint32_t addr) {
    uint4 r;
    asm volatile("ld.shared.v4.u32 {%0,%1,%2,%3}, [%4];" : "=r"(r.x), "=r"(r.y), "=r"(r.z), "=r"(r.w) : "r"(addr) : "memory");
    return r;
}
__device__ __forceinline__ void wait_until(unsigned t0, int t) {
#pragma unroll 1
    for (int n = 0; n < SPIN_LIMIT; n++) if ((int)(gtime32() - t0) >= t) break;
}
__device__ __forceinline__ void spin_cycles(int n) {
    if (n > 0) { const unsigned c0 = clock(); while ((int)(clock() - c0) < n) {} }
}
__device__ __forceinline__ float octet_reduce(float v0, float v1, float v2, float v3, int lane) {
    const unsigned FULL = 0xffffffffu;
    const unsigned b1 = lane & 2, b2 = lane & 4;
    float k0 = selp(v2, v0, b1), k1 = selp(v3, v1, b1);
    const float s0 = selp(v0, v2, b1), s1 = selp(v1, v3, b1);
    k0 += __shfl_xor_sync(FULL, s0, 2);
    k1 += __shfl_xor_sync(FULL, s1, 2);
    float k = selp(k1, k0, b2);
    const float s = selp(k0, k1, b2);
    k += __shfl_xor_sync(FULL, s, 4);
    k += __shfl_xor_sync(FULL, k, 8);
    k += __shfl_xor_sync(FULL, k, 16);
    return k;
}

constexpr int NB_XN = 1, NB_QPART = 2, NB_Q = 3, NB_ATT = 4, NB_FPART = 5, NB_DSENT = 6, NB_H1 = 7, NB_PROBE = 8, NB_TAG0 = 9, NB_TAG1 = 10, NB_HP = 11;
constexpr int N_XN = NTHREADS - 64;

__global__ void __launch_bounds__(NTHREADS, 1)
fused_decode_kernel(const __nv_bfloat16* __restrict__ x, const __nv_bfloat16* __restrict__ wq,
                    const __nv_bfloat16* __restrict__ kc,
                    const __nv_bfloat16* __restrict__ w2, __nv_bfloat16* __restrict__ out, unsigned* __restrict__ scr,
                    const __grid_constant__ CUtensorMap map_v, const __grid_constant__ CUtensorMap map_w1,
                    const __grid_constant__ CUtensorMap map_wo) {
    constexpr Pace pc = PACE_DEFAULT;
    extern __shared__ __align__(1024) unsigned char smem[];
    const unsigned tstart = gtime32();
    const int tid = threadIdx.x, warp = tid >> 5, lane = tid & 31;
    const int b = blockIdx.x, h = b >> 2, c = b & 3;
    const int cw = warp - 2, ct = tid - 64;

    uint2 xr[5];
    unsigned epoch;
    uint4 wr[10];
    {
        const char* wp = reinterpret_cast<const char*>(wq) + (size_t)(160 * c + (ct >> 4)) * 8192 + h * 256 + (ct & 15) * 16;
        const uint2* xp = reinterpret_cast<const uint2*>(x) + lane;
        asm volatile("{\n.reg .pred p;\nsetp.ne.u32 p, %13, 0;\n@p bra.uni XSKIP;\n"
                     "ld.global.nc.v2.u32 {%0,%1}, [%11];\nld.global.nc.v2.u32 {%2,%3}, [%11+256];\nld.global.nc.v2.u32 {%4,%5}, [%11+512];\n"
                     "ld.global.nc.v2.u32 {%6,%7}, [%11+768];\nld.global.nc.v2.u32 {%8,%9}, [%11+1024];\n"
                     "ld.relaxed.gpu.global.u32 %10, [%12];\nXSKIP:\n}"
                     : "=r"(xr[0].x), "=r"(xr[0].y), "=r"(xr[1].x), "=r"(xr[1].y), "=r"(xr[2].x), "=r"(xr[2].y), "=r"(xr[3].x), "=r"(xr[3].y),
                       "=r"(xr[4].x), "=r"(xr[4].y), "=r"(epoch)
                     : "l"(xp), "l"(scr + PR_EPOCH * PAIR_W), "r"(warp) : "memory");
        asm volatile("{\n.reg .pred p;\nsetp.ge.u32 p, %41, 8;\n@p bra.uni WSKIP;\n"
                     "ld.global.nc.L1::no_allocate.v4.u32 {%0,%1,%2,%3}, [%40];\n"
                     "ld.global.nc.L1::no_allocate.v4.u32 {%4,%5,%6,%7}, [%40+131072];\n"
                     "ld.global.nc.L1::no_allocate.v4.u32 {%8,%9,%10,%11}, [%40+262144];\n"
                     "ld.global.nc.L1::no_allocate.v4.u32 {%12,%13,%14,%15}, [%40+393216];\n"
                     "ld.global.nc.L1::no_allocate.v4.u32 {%16,%17,%18,%19}, [%40+524288];\n"
                     "ld.global.nc.L1::no_allocate.v4.u32 {%20,%21,%22,%23}, [%40+655360];\n"
                     "ld.global.nc.L1::no_allocate.v4.u32 {%24,%25,%26,%27}, [%40+786432];\n"
                     "ld.global.nc.L1::no_allocate.v4.u32 {%28,%29,%30,%31}, [%40+917504];\n"
                     "ld.global.nc.L1::no_allocate.v4.u32 {%32,%33,%34,%35}, [%40+1048576];\n"
                     "ld.global.nc.L1::no_allocate.v4.u32 {%36,%37,%38,%39}, [%40+1179648];\n"
                     "WSKIP:\n}"
                     : "=r"(wr[0].x), "=r"(wr[0].y), "=r"(wr[0].z), "=r"(wr[0].w), "=r"(wr[1].x), "=r"(wr[1].y), "=r"(wr[1].z), "=r"(wr[1].w),
                       "=r"(wr[2].x), "=r"(wr[2].y), "=r"(wr[2].z), "=r"(wr[2].w), "=r"(wr[3].x), "=r"(wr[3].y), "=r"(wr[3].z), "=r"(wr[3].w),
                       "=r"(wr[4].x), "=r"(wr[4].y), "=r"(wr[4].z), "=r"(wr[4].w), "=r"(wr[5].x), "=r"(wr[5].y), "=r"(wr[5].z), "=r"(wr[5].w),
                       "=r"(wr[6].x), "=r"(wr[6].y), "=r"(wr[6].z), "=r"(wr[6].w), "=r"(wr[7].x), "=r"(wr[7].y), "=r"(wr[7].z), "=r"(wr[7].w),
                       "=r"(wr[8].x), "=r"(wr[8].y), "=r"(wr[8].z), "=r"(wr[8].w), "=r"(wr[9].x), "=r"(wr[9].y), "=r"(wr[9].z), "=r"(wr[9].w)
                     : "l"(wp), "r"(cw));
    }
    if (ct == 0) TL(15);

    const uint32_t sb = smem_u32(smem);
    const uint32_t bars = sb + SM_BAR;
    const int g = lane >> 2, t = lane & 3;
    const unsigned FULL = 0xffffffffu;
    volatile unsigned* const misc = reinterpret_cast<volatile unsigned*>(smem + SM_TAG);
    const int f = (b >= NWO) ? b - NWO : b + (NCTA - NWO);

    if ((unsigned)cw < 10u) {
        const int mi = lane >> 3, ri = lane & 7;
        unsigned tag, side, sd0, sd1;
        const int oct = 2 * (4 * cw + t);
        const unsigned xpair = __ldg(reinterpret_cast<const unsigned*>(x) + ct);
        if (cw < 8) {
            bar_sync(NB_XN, N_XN);
            tag = misc[0];
            unsigned* const o_dst = pin(scr + (PR_O + h) * PAIR_W + (t >> 1) * REP_W + c * 160 + 16 * cw + 8 * (t & 1) + g);
            unsigned* const ml_dst = scr + (PR_O + h) * PAIR_W + ((lane >> 3) & 1) * REP_W + c * 160 + 128 + (lane & 7);
            st_w1(o_dst, 0u);
            if (cw == 0 && lane < 16) st_w1(ml_dst, 0u);
            {
                const float* xn = reinterpret_cast<const float*>(smem + SM_XN) + 160 * c + (ct >> 4);
                float acc[8];
#pragma unroll
                for (int j = 0; j < 8; j++) acc[j] = 0.f;
#pragma unroll
                for (int i = 0; i < 10; i++) {
                    const float xv = xn[16 * i];
                    acc[0] = fmaf(xv, bf_lo(wr[i].x), acc[0]); acc[1] = fmaf(xv, bf_hi(wr[i].x), acc[1]);
                    acc[2] = fmaf(xv, bf_lo(wr[i].y), acc[2]); acc[3] = fmaf(xv, bf_hi(wr[i].y), acc[3]);
                    acc[4] = fmaf(xv, bf_lo(wr[i].z), acc[4]); acc[5] = fmaf(xv, bf_hi(wr[i].z), acc[5]);
                    acc[6] = fmaf(xv, bf_lo(wr[i].w), acc[6]); acc[7] = fmaf(xv, bf_hi(wr[i].w), acc[7]);
                }
#pragma unroll
                for (int j = 0; j < 8; j++) acc[j] += __shfl_xor_sync(FULL, acc[j], 16);
                if (lane < 16) {
                    float4* qp = reinterpret_cast<float4*>(smem + SM_QPART + cw * 512 + lane * 32);
                    qp[0] = make_float4(acc[0], acc[1], acc[2], acc[3]);
                    qp[1] = make_float4(acc[4], acc[5], acc[6], acc[7]);
                }
            }
            bar_arrive(NB_QPART, 288);
            if (pc.mode == 1) return;
            bar_sync(NB_Q, 288);
            uint4 qf[4];
#pragma unroll
            for (int j = 0; j < 4; j++) qf[j] = lds16(sb + SM_QS + 16 * (t + 4 * (j ^ (g & 1))));
            float mys = 0.f;
#pragma unroll 1
            for (int tile = 0; tile < 2; tile++) {
                const int ch = cw + 8 * tile;
                mbar_wait(bars + (BAR_K + ch) * 8);
                const uint32_t kb = sb + SM_K + ch * 4096 + g * 256 + t * 16;
                float cA[4] = {0.f, 0.f, 0.f, 0.f}, cB[4] = {0.f, 0.f, 0.f, 0.f};
#pragma unroll
                for (int j = 0; j < 4; j++) {
                    const uint32_t a = kb + 64 * (j ^ (g & 1));
                    const uint4 ra = lds16(a), rb = lds16(a + 2048);
                    mma16816(cA, ra.x, rb.x, ra.y, rb.y, qf[j].x, qf[j].y);
                    mma16816(cB, ra.z, rb.z, ra.w, rb.w, qf[j].z, qf[j].w);
                }
                const float s0 = selp(cA[1] + cB[1], cA[0] + cB[0], g & 1);
                const float s1 = selp(cA[3] + cB[3], cA[2] + cB[2], g & 1);
                mys = selp(selp(s1, s0, t & 1), mys, (t >> 1) == tile);
            }
            __syncwarp();
            if (lane == 0) mbar_arrive(bars + BAR_KFREE * 8);
            mys = bfr(bfr(mys) * 0.08838834764831845f);
            if (ct == 224) TL(3);
            {
                float* const ml = reinterpret_cast<float*>(smem + SM_ML);
                float m = mys;
#pragma unroll
                for (int o = 16; o; o >>= 1) m = fmaxf(m, __shfl_xor_sync(FULL, m, o));
                if (lane == 0) ml[cw] = m;
                bar_sync(NB_ATT, 256);
                const float4 m0 = reinterpret_cast<const float4*>(ml)[0], m1 = reinterpret_cast<const float4*>(ml)[1];
                m = fmaxf(fmaxf(fmaxf(m0.x, m0.y), fmaxf(m0.z, m0.w)), fmaxf(fmaxf(m1.x, m1.y), fmaxf(m1.z, m1.w)));
                const unsigned pb = pack_bf(__expf(mys - m), 0.f);
                *reinterpret_cast<unsigned short*>(smem + SM_P + (g >> 1) * 144 + (cw + 8 * (t >> 1)) * 8 + (t & 1) * 4 + (g & 1) * 2) = (unsigned short)pb;
                float l = bf_lo(pb);
#pragma unroll
                for (int o = 16; o; o >>= 1) l += __shfl_xor_sync(FULL, l, o);
                if (lane == 0) ml[8 + cw] = l;
                bar_sync(NB_ATT, 256);
                if (cw == 0) {
                    const float4 l0 = reinterpret_cast<const float4*>(ml)[2], l1 = reinterpret_cast<const float4*>(ml)[3];
                    l = ((l0.x + l0.y) + (l0.z + l0.w)) + ((l1.x + l1.y) + (l1.z + l1.w));
                    if (lane < 16) st_w1(ml_dst, tagw((lane & 1) ? l : m, tag));
                }
                if (ct == 224) TL(5);
            }
            {
                uint4 pf[8];
#pragma unroll
                for (int i = 0; i < 8; i++) pf[i] = lds16(sb + SM_P + t * 144 + i * 16);
                const uint32_t va = sb + SM_V + (cw >> 2) * 2048 + ((mi >> 1) * 8 + ri) * 128 + (((2 * (cw & 3) + (mi & 1)) ^ ri) * 16);
                float cA[4] = {0.f, 0.f, 0.f, 0.f}, cB[4] = {0.f, 0.f, 0.f, 0.f};
#pragma unroll
                for (int i = 0; i < 8; i++) {
                    mbar_wait(bars + (BAR_V + i) * 8);
                    const uint4 a0 = ldsm4t(va + i * 8192), a1 = ldsm4t(va + i * 8192 + 4096);
                    mma16816(cA, a0.x, a0.y, a0.z, a0.w, pf[i].x, pf[i].y);
                    mma16816(cB, a1.x, a1.y, a1.z, a1.w, pf[i].z, pf[i].w);
                }
                st_w1(o_dst, tagw(selp(cA[2] + cB[2], cA[0] + cB[0], t & 1), tag));
                if (ct == 0) TL(4);
            }
            mbar_wait(bars + BAR_SIDE * 8);
            side = misc[1];
            sd0 = ld_w1(scr + near_off(PR_SIDE, side) + oct * 8); sd1 = ld_w1(scr + near_off(PR_SIDE, side) + oct * 8 + 8);
            if (b < NWO) {
                const int ks = cw >> 1;
                const uint32_t ab = sb + SM_K + (cw & 1) * 4096 + (16 * ks + (mi >> 1) * 8 + ri) * 64;
                const uint32_t ab0 = ab + (((mi & 1) ^ ((ri >> 1) & 3)) * 16), ab1 = ab + (((2 + (mi & 1)) ^ ((ri >> 1) & 3)) * 16);
                uint4 a[2 * NPRE];
#pragma unroll
                for (int i = 0; i < NPRE; i++) {
                    mbar_wait(bars + (BAR_WO + i) * 8);
                    a[2 * i] = ldsm4t(ab0 + i * 8192); a[2 * i + 1] = ldsm4t(ab1 + i * 8192);
                }
                mbar_wait(bars + BAR_O * 8);
                uint4 bf[4];
#pragma unroll
                for (int i = 0; i < 4; i++) bf[i] = lds16(sb + SM_OF + (ks * 4 + t) * 144 + (cw & 1) * 64 + i * 16);
                float cc[4][4];
#pragma unroll
                for (int i = 0; i < 4; i++) cc[i][0] = cc[i][1] = cc[i][2] = cc[i][3] = 0.f;
#pragma unroll
                for (int i = 0; i < 8; i++) {
                    uint4 a0, a1;
                    if (i < NPRE) { a0 = a[2 * i]; a1 = a[2 * i + 1]; }
                    else {
                        mbar_wait(bars + (BAR_WO + i) * 8);
                        a0 = ldsm4t(ab0 + i * 8192); a1 = ldsm4t(ab1 + i * 8192);
                    }
                    const unsigned b0 = (i & 1) ? bf[i >> 1].z : bf[i >> 1].x, b1 = (i & 1) ? bf[i >> 1].w : bf[i >> 1].y;
                    mma16816(cc[2 * (i & 1)], a0.x, a0.y, a0.z, a0.w, b0, b1);
                    mma16816(cc[2 * (i & 1) + 1], a1.x, a1.y, a1.z, a1.w, b0, b1);
                }
                sts_p(sb + SM_HP + ((8 * t + g) * 12 + cw) * 4,
                      sel4(cc[0][0] + cc[2][0], cc[0][2] + cc[2][2], cc[1][0] + cc[3][0], cc[1][2] + cc[3][2], t), 1u);
                bar_arrive(NB_HP, 288);
                if (ct == 0) TL(6);
            }
        } else {
            unsigned* const probe = scr + near_off(PR_PROBE + (b >> 2), cw & 1) + (b & 3) * 256;
            st_w1(probe + (lane >> 3) * 32 + (lane & 7), 0u);
            st_w1(probe + 128 + (lane >> 3) * 32 + (lane & 7), 0u);
            if (cw == 8 && lane == 0) misc[2] = 0u;
            wait_until(tstart, pc.tP);
            bar_sync(NB_PROBE, 64);
            unsigned v = 0;
#pragma unroll 1
            for (int i = 0; i < pc.nprobe; i++) v = ld_w1(probe + i * 32 + v);
            unsigned won = 0;
            if (lane == 0) won = (atomicExch(reinterpret_cast<unsigned*>(smem + SM_TAG) + 2, 1u + v) == 0u);
            won = __shfl_sync(FULL, won, 0);
            if (cw & 1) bar_sync(NB_TAG1, 64); else bar_sync(NB_TAG0, 64);
            tag = misc[0];
            if (pc.mode == 1) return;
            if (won) {
                const unsigned sd = cw & 1;
                if (lane == 0) {
                    misc[1] = sd;
                    mbar_arrive(bars + BAR_SIDE * 8);
                    TL(23);
                }
                if (f < NOCT) {
                    unsigned* i1 = scr + near_off(PR_D + f, sd) + 4 * lane;
#pragma unroll
                    for (int j = 0; j < 7; j++) {
                        const unsigned z = (j * 16 + (lane >> 1) >= NFFN) ? tag : 0u;
                        st_w4(i1 + 128 * j, make_uint4(z, z, z, z));
                    }
                    asm volatile("fence.acq_rel.gpu;" ::: "memory");
                    __syncwarp();
                    if (lane < 16) st_w1(scr + PR_SIDE * PAIR_W + (lane >> 3) * REP_W + f * 8 + (lane & 7), (sd << 2) | tag);
                    if (lane == 0) { mbar_arrive(bars + BAR_CLR * 8); TL(30); }
                }
            }
            mbar_wait(bars + (BAR_V + 4) * 8);
            mbar_wait(bars + BAR_SIDE * 8);
            side = misc[1];
            sd0 = ld_w1(scr + near_off(PR_SIDE, side) + oct * 8); sd1 = ld_w1(scr + near_off(PR_SIDE, side) + oct * 8 + 8);
            if (b < NWO) {
                const int h0 = 8 * (b / 20) + 4 * (cw & 1);
                const unsigned* po[4];
#pragma unroll
                for (int u = 0; u < 4; u++) po[u] = scr + near_off(PR_O + h0 + u, side) + 4 * lane;
                float fac;
                {
                    const unsigned* ps = scr + near_off(PR_O + h0 + ((lane >> 2) & 3), side) + 160 * (lane & 3) + 128;
                    uint2 sv = ld_w2(ps);
#pragma unroll 1
                    for (int n = 0; n < SPIN_LIMIT; n++) {
                        if (!__any_sync(FULL, bad2(sv, tag))) break;
                        __nanosleep(50);
                        sv = ld_w2(ps);
                    }
                    const float m = untag(sv.x);
                    float M = fmaxf(m, __shfl_xor_sync(FULL, m, 1));
                    M = fmaxf(M, __shfl_xor_sync(FULL, M, 2));
                    fac = __expf(m - M);
                    float l = fac * untag(sv.y);
                    l += __shfl_xor_sync(FULL, l, 1);
                    l += __shfl_xor_sync(FULL, l, 2);
                    fac *= fast_rcp(l);
                }
                float fq[16];
#pragma unroll
                for (int i = 0; i < 16; i++) fq[i] = __shfl_sync(FULL, fac, i);
                unsigned* of = reinterpret_cast<unsigned*>(smem + SM_OF) + (((lane >> 2) & 3) * 4 + 2 * (lane & 1)) * 36 +
                               (lane >> 4) * 16 + 8 * (cw & 1) + ((lane >> 1) & 1);
                mbar_wait(bars + (BAR_V + 7) * 8);
                spin_cycles(pc.dlyO);
                uint4 ov[16];
#pragma unroll
                for (int i = 0; i < 16; i++) ov[i] = ld_w4(po[i >> 2] + 160 * (i & 3));
#pragma unroll 1
                for (int n = 0; n < SPIN_LIMIT; n++) {
                    bool miss = false;
#pragma unroll
                    for (int i = 0; i < 16; i++) if (bad4(ov[i], tag)) { ov[i] = ld_w4(po[i >> 2] + 160 * (i & 3)); miss = true; }
                    if (!__any_sync(FULL, miss)) break;
                }
#pragma unroll
                for (int u = 0; u < 4; u++) {
                    const uint4 *v = ov + 4 * u;
                    const float* fu = fq + 4 * u;
                    const float r0 = (fu[0] * __uint_as_float(v[0].x) + fu[1] * __uint_as_float(v[1].x)) + (fu[2] * __uint_as_float(v[2].x) + fu[3] * __uint_as_float(v[3].x));
                    const float r1 = (fu[0] * __uint_as_float(v[0].y) + fu[1] * __uint_as_float(v[1].y)) + (fu[2] * __uint_as_float(v[2].y) + fu[3] * __uint_as_float(v[3].y));
                    const float r2 = (fu[0] * __uint_as_float(v[0].z) + fu[1] * __uint_as_float(v[1].z)) + (fu[2] * __uint_as_float(v[2].z) + fu[3] * __uint_as_float(v[3].z));
                    const float r3 = (fu[0] * __uint_as_float(v[0].w) + fu[1] * __uint_as_float(v[1].w)) + (fu[2] * __uint_as_float(v[2].w) + fu[3] * __uint_as_float(v[3].w));
                    of[2 * u] = pack_bf(r0, r1);
                    of[2 * u + 36] = pack_bf(r2, r3);
                }
                __syncwarp();
                if (lane == 0) { mbar_arrive(bars + BAR_O * 8); if (cw == 8) TL(29); }
            }
        }
        if (f >= NFFN) return;

        const unsigned* const sd_src = scr + near_off(PR_SIDE, side) + oct * 8;
        const unsigned* const h_src0 = pin(scr + near_off(PR_H + 4 * (b & 1), side) + 2 * ct);
        const unsigned* const h_src1 = pin(scr + near_off(PR_H + 4 * (b & 1) + 1, side) + 2 * ct);
        const unsigned* const h_src2 = pin(scr + near_off(PR_H + 4 * (b & 1) + 2, side) + 2 * ct);
        const unsigned* const h_src3 = pin(scr + near_off(PR_H + 4 * (b & 1) + 3, side) + 2 * ct);
#pragma unroll 1
        for (int n = 0; n < SPIN_LIMIT; n++) {
            if (!__any_sync(FULL, (sd0 & sd1 & tag) == 0)) break;
            __nanosleep(100);
            sd0 = ld_w1(sd_src); sd1 = ld_w1(sd_src + 8);
        }
        unsigned* const d_a = pin(scr + near_off(PR_D + oct, sd0 >> 2) + f * 8 + g);
        unsigned* const d_b = pin(scr + near_off(PR_D + oct + 1, sd1 >> 2) + f * 8 + g);
        uint32_t dp_w = sb + SM_DP + ((g + 8 * t) * 12 + cw) * 4;
        uint32_t st_w = sb + SM_DP + ((32 + lane) * 12 + cw) * 4;
        uint32_t w2_r = sb + SM_W2 + ((mi >> 1) * 8 + ri) * ROW_PITCH + cw * 128 + (mi & 1) * 16;
        uint32_t w1_r = sb + SM_W1 + (64 * cw + (mi >> 1) * 8 + ri) * 32 + (((mi & 1) ^ (ri >> 2)) * 16);
        uint32_t w1_bar = bars + (BAR_W1 + (cw >> 1)) * 8;
        asm volatile("" : "+r"(dp_w), "+r"(st_w), "+r"(w2_r), "+r"(w1_r), "+r"(w1_bar));
        mbar_wait(bars + ((b < NWO) ? BAR_WO + 7 : BAR_W1) * 8);
        uint2 h0 = ld_w2(h_src0), h1 = ld_w2(h_src1), h2 = ld_w2(h_src2), h3 = ld_w2(h_src3);
        uint4 a[4];
        bool w1_in = false;
#pragma unroll 1
        for (int n = 0; n < SPIN_LIMIT; n++) {
            if (!w1_in && mbar_test(w1_bar)) {
                w1_in = true;
#pragma unroll
                for (int s = 0; s < 4; s++) a[s] = ldsm4t(w1_r + s * 512);
            }
            bool miss = false;
            if (bad2(h0, tag)) { h0 = ld_w2(h_src0); miss = true; }
            if (bad2(h1, tag)) { h1 = ld_w2(h_src1); miss = true; }
            if (bad2(h2, tag)) { h2 = ld_w2(h_src2); miss = true; }
            if (bad2(h3, tag)) { h3 = ld_w2(h_src3); miss = true; }
            if (!__any_sync(FULL, miss)) break;
        }
        const unsigned att = pack_bf((__uint_as_float(h0.x) + __uint_as_float(h1.x)) + (__uint_as_float(h2.x) + __uint_as_float(h3.x)),
                                     (__uint_as_float(h0.y) + __uint_as_float(h1.y)) + (__uint_as_float(h2.y) + __uint_as_float(h3.y)));
        const unsigned hpair = pack_bf(bf_lo(xpair) + bf_lo(att), bf_hi(xpair) + bf_hi(att));
        if (ct == 0) TL(8);
        unsigned hf[8];
#pragma unroll
        for (int s = 0; s < 8; s++) hf[s] = __shfl_sync(FULL, hpair, 4 * s + t);
        {
            float sA[4] = {0.f, 0.f, 0.f, 0.f}, sB[4] = {0.f, 0.f, 0.f, 0.f};
#pragma unroll
            for (int s = 0; s < 4; s += 2) {
                mma16816(sA, hf[2 * s], 0x3F803F80u, hf[2 * s + 1], 0x3F803F80u, hf[2 * s], hf[2 * s + 1]);
                mma16816(sB, hf[2 * s + 2], 0x3F803F80u, hf[2 * s + 3], 0x3F803F80u, hf[2 * s + 2], hf[2 * s + 3]);
            }
            if (!w1_in) {
                mbar_wait(w1_bar);
#pragma unroll
                for (int s = 0; s < 4; s++) a[s] = ldsm4t(w1_r + s * 512);
            }
            float dA[4] = {0.f, 0.f, 0.f, 0.f}, dB[4] = {0.f, 0.f, 0.f, 0.f};
#pragma unroll
            for (int s = 0; s < 8; s++) hf[s] = (g < 4) ? hf[s] : 0x3F803F80u;
#pragma unroll
            for (int s = 0; s < 4; s += 2) {
                mma16816(dA, a[s].x, a[s].y, a[s].z, a[s].w, hf[2 * s], hf[2 * s + 1]);
                mma16816(dB, a[s + 1].x, a[s + 1].y, a[s + 1].z, a[s + 1].w, hf[2 * s + 2], hf[2 * s + 3]);
            }
            sts_p(st_w, selp(sA[2] + sB[2], sA[0] + sB[0], lane), lane < 2);
            sts_p(dp_w, selp(dA[2] + dB[2], dA[0] + dB[0], t & 1), 1u);
        }
        if (ct == 0) TL(7);
        bar_arrive(NB_FPART, 352);
        uint4 w[4];
        mbar_wait(bars + BAR_W2 * 8);
#pragma unroll
        for (int j = 0; j < 4; j++) w[j] = ldsm4t(w2_r + j * 32);
        bar_sync(NB_H1, 352);
        unsigned b0, b1;
        asm volatile("ld.shared.u32 %0, [%1];" : "=r"(b0) : "r"(sb + SM_H1 + 4 * t) : "memory");
        asm volatile("ld.shared.u32 %0, [%1];" : "=r"(b1) : "r"(sb + SM_H1 + 16 + 4 * t) : "memory");
        float y[4][4];
#pragma unroll
        for (int j = 0; j < 4; j++) {
            y[j][0] = y[j][1] = y[j][2] = y[j][3] = 0.f;
            mma16816(y[j], w[j].x, w[j].y, w[j].z, w[j].w, b0, b1);
        }
        st_w1(d_a, tagw(sel4(y[0][0], y[1][0], y[2][0], y[3][0], t), tag));
        st_w1(d_b, tagw(sel4(y[0][2], y[1][2], y[2][2], y[3][2], t), tag));
        if (ct == 0) TL(9);
        if (f < NOCT) bar_arrive(NB_DSENT, 352);
    } else if (warp == 1) {
        const unsigned t0 = tstart + (unsigned)((h & 7) * pc.stag);
        if (lane == 0) {
            TLV(0, tstart);
#pragma unroll
            for (int i = 0; i < BAR_KFREE; i++) mbar_init(bars + i * 8, 1);
            mbar_init(bars + BAR_KFREE * 8, 8);
            mbar_init(bars + BAR_O * 8, 2);
            asm volatile("fence.mbarrier_init.release.cluster;" ::: "memory");
            asm volatile("prefetch.tensormap [%0];" :: "l"(&map_v) : "memory");
            asm volatile("prefetch.tensormap [%0];" :: "l"(&map_w1) : "memory");
            asm volatile("prefetch.tensormap [%0];" :: "l"(&map_wo) : "memory");
        }
        bar_arrive(NB_XN, N_XN);
        if (lane == 0) {
            int tt = pc.tK;
            const uint64_t pol = stream_policy();
            const char* ks = reinterpret_cast<const char*>(kc) + (size_t)h * 1048576 + 786432 + c * 65536;
#pragma unroll 1
            for (int ii = 0; ii < 16; ii++) {
                const int i = ii;
                wait_until(t0, tt); tt += pc.dKV;
                mbar_expect_tx(bars + (BAR_K + i) * 8, 4096);
                bulk_g2s(sb + SM_K + i * 4096, ks + i * 4096, 4096, bars + (BAR_K + i) * 8, pol);
            }
#pragma unroll 1
            for (int ii = 0; ii < 16; ii++) {
                const int i = ii;
                wait_until(t0, tt); tt += pc.dKV;
                if (!(i & 1)) mbar_expect_tx(bars + (BAR_V + (i >> 1)) * 8, 8192);
                tma3d(sb + SM_V + i * 4096, &map_v, 0, h * 4096 + 3072 + 256 * c + 16 * i, 0, bars + (BAR_V + (i >> 1)) * 8, pol);
            }
            if (b < NWO) {
                const int c0 = 32 * (b % 20), r0 = 1024 * (b / 20);
                if (pc.mode != 1) mbar_wait(bars + BAR_KFREE * 8);
#pragma unroll 1
                for (int i = 0; i < 16; i++) {
                    wait_until(t0, tt + i * pc.dWO);
                    if (!(i & 1)) mbar_expect_tx(bars + (BAR_WO + (i >> 1)) * 8, 8192);
                    tma2d(sb + SM_K + i * 4096, &map_wo, c0, r0 + 64 * i, bars + (BAR_WO + (i >> 1)) * 8, pol);
                }
            }
            tt += 16 * pc.dWO + pc.gap;
            if (f < NFFN) {
#pragma unroll 1
                for (int j = 0; j < 5; j++) {
                    wait_until(t0, tt); tt += pc.dW1;
                    mbar_expect_tx(bars + (BAR_W1 + j) * 8, 4096);
                    tma2d(sb + SM_W1 + j * 4096, &map_w1, 16 * f, 128 * j, bars + (BAR_W1 + j) * 8, pol);
                }
                const char* w2s = reinterpret_cast<const char*>(w2) + (size_t)f * 16 * 1280;
                mbar_expect_tx(bars + BAR_W2 * 8, 16 * 1280);
#pragma unroll 1
                for (int j = 0; j < 4; j++) {
                    wait_until(t0, tt); tt += pc.dW2;
#pragma unroll
                    for (int i = 0; i < 4; i++) {
                        const int r = j * 4 + i;
                        bulk_g2s(sb + SM_W2 + r * ROW_PITCH, w2s + r * 1280, 1280, bars + BAR_W2 * 8, pol);
                    }
                }
                TL(10);
            }
            if (pc.mode == 1) {
                for (int i = 0; i < BAR_SIDE; i++)
                    if (i < BAR_V + 8 || (i >= BAR_WO && (i < BAR_W1 ? b < NWO : f < NFFN))) mbar_wait(bars + i * 8);
            }
        }
    } else {
        const int col = 8 * f + 4 * (lane & 1) + (lane & 2) + ((lane >> 2) & 1);
        float xcol = 0.f;
        if (f < NOCT) xcol = __bfloat162float(x[col]);
        {
            float s = 0.f;
#pragma unroll
            for (int j = 0; j < 5; j++) s += (bf_lo(xr[j].x) + bf_hi(xr[j].x)) + (bf_lo(xr[j].y) + bf_hi(xr[j].y));
#pragma unroll
            for (int o = 16; o; o >>= 1) s += __shfl_xor_sync(FULL, s, o);
            const float mean = s * (1.0f / 640.0f);
            float v = 0.f;
#pragma unroll
            for (int j = 0; j < 5; j++) {
                float d0 = bf_lo(xr[j].x) - mean, d1 = bf_hi(xr[j].x) - mean, d2 = bf_lo(xr[j].y) - mean, d3 = bf_hi(xr[j].y) - mean;
                v += (d0 * d0 + d1 * d1) + (d2 * d2 + d3 * d3);
            }
#pragma unroll
            for (int o = 16; o; o >>= 1) v += __shfl_xor_sync(FULL, v, o);
            const float mb = bfr(mean);
            const float rb = __frcp_rn(bfr(__fsqrt_rn(bfr(bfr(v * (1.0f / 640.0f)) + 1e-5f))));
            float4* xn = reinterpret_cast<float4*>(smem + SM_XN);
#pragma unroll
            for (int j = 0; j < 5; j++) {
                float4 o;
                o.x = bfr(bfr(bf_lo(xr[j].x) - mb) * rb); o.y = bfr(bfr(bf_hi(xr[j].x) - mb) * rb);
                o.z = bfr(bfr(bf_lo(xr[j].y) - mb) * rb); o.w = bfr(bfr(bf_hi(xr[j].y) - mb) * rb);
                xn[j * 32 + lane] = o;
            }
        }
        const unsigned tag = 1u + (epoch & 1u);
        if (lane == 0) misc[0] = tag;
        if (lane == 0) TL(22);
        bar_sync(NB_XN, N_XN);
        bar_arrive(NB_TAG0, 64);
        bar_arrive(NB_TAG1, 64);
        unsigned* const a_dst = scr + (PR_A + (h >> 1)) * PAIR_W + (b & 7) * 128 + 4 * lane;
        unsigned* const h_dst = pin(scr + (PR_H + b / 20) * PAIR_W + 32 * (b % 20) + lane);
        st_w4(a_dst, make_uint4(0u, 0u, 0u, 0u));
        st_w4(a_dst + REP_W, make_uint4(0u, 0u, 0u, 0u));
        if (b < NWO) { st_w1(h_dst, 0u); st_w1(h_dst + REP_W, 0u); st_w1(h_dst + 4 * PAIR_W, 0u); st_w1(h_dst + 4 * PAIR_W + REP_W, 0u); }
        bar_sync(NB_QPART, 288);
        {
            const float4* qp = reinterpret_cast<const float4*>(smem + SM_QPART) + lane;
            float4 s = qp[0];
            if (lane == 0) TLD(1, s.x);
#pragma unroll
            for (int w = 1; w < 8; w++) { const float4 u = qp[w * 32]; s.x += u.x; s.y += u.y; s.z += u.z; s.w += u.w; }
            const uint4 mine = make_uint4(tagw(s.x, tag), tagw(s.y, tag), tagw(s.z, tag), tagw(s.w, tag));
            st_w4(a_dst, mine);
            st_w4(a_dst + REP_W, mine);
            if (pc.mode == 1) return;
            mbar_wait(bars + BAR_SIDE * 8);
            const unsigned* pa = scr + near_off(PR_A + (h >> 1), misc[1]) + (h & 1) * 512 + 4 * lane;
            uint4 v[4];
#pragma unroll 1
            for (int n = 0; n < SPIN_LIMIT; n++) {
#pragma unroll
                for (int cc = 0; cc < 4; cc++) v[cc] = (cc == c) ? mine : ld_w4(pa + cc * 128);
                if (!__any_sync(FULL, bad4(v[0], tag) | bad4(v[1], tag) | bad4(v[2], tag) | bad4(v[3], tag))) break;
                __nanosleep(50);
            }
            const float q0 = ((untag(v[0].x) + untag(v[1].x)) + untag(v[2].x)) + untag(v[3].x);
            const float q1 = ((untag(v[0].y) + untag(v[1].y)) + untag(v[2].y)) + untag(v[3].y);
            const float q2 = ((untag(v[0].z) + untag(v[1].z)) + untag(v[2].z)) + untag(v[3].z);
            const float q3 = ((untag(v[0].w) + untag(v[1].w)) + untag(v[2].w)) + untag(v[3].w);
            reinterpret_cast<uint2*>(smem + SM_QS)[lane] = make_uint2(pack_bf(q0, q1), pack_bf(q2, q3));
        }
        bar_arrive(NB_Q, 288);
        if (lane == 0) TL(2);
        const unsigned side = misc[1];
        const unsigned* const d_src = pin(scr + near_off(PR_D + f, side) + 4 * lane);
        const unsigned* const hb0 = pin(scr + near_off(PR_H + 4 * (b & 1) + (lane >> 3), side) + col);
        __nv_bfloat16* const o_dst = pin(out + col);
        int lane_p = lane, dly_d = pc.dlyD;
        uint32_t hp_r = sb + SM_HP + lane * 48;
        asm volatile("" : "+r"(lane_p), "+r"(dly_d), "+r"(hp_r));
        if (b < NWO) {
            bar_sync(NB_HP, 288);
            const uint4 u0 = lds16(hp_r), u1 = lds16(hp_r + 16);
            const unsigned hw = tagw(((__uint_as_float(u0.x) + __uint_as_float(u0.y)) + (__uint_as_float(u0.z) + __uint_as_float(u0.w))) +
                                     ((__uint_as_float(u1.x) + __uint_as_float(u1.y)) + (__uint_as_float(u1.z) + __uint_as_float(u1.w))), tag);
            st_w1(h_dst, hw); st_w1(h_dst + REP_W, hw); st_w1(h_dst + 4 * PAIR_W, hw); st_w1(h_dst + 4 * PAIR_W + REP_W, hw);
            if (lane_p == 0) TL(12);
        }
        if (f >= NFFN) return;
        {
            uint32_t dp_r = sb + SM_DP + lane * 48, st_r = sb + SM_DP + (32 + (lane & 1)) * 48, h1_w = sb + SM_H1 + 2 * lane;
            asm volatile("" : "+r"(dp_r), "+r"(st_r), "+r"(h1_w));
            bar_sync(NB_FPART, 352);
            const uint4 s0 = lds16(st_r), s1 = lds16(st_r + 16), u0 = lds16(dp_r), u1 = lds16(dp_r + 16);
            float s2x, s2y, u2x, u2y;
            asm volatile("ld.shared.v2.f32 {%0,%1}, [%2];" : "=f"(s2x), "=f"(s2y) : "r"(st_r + 32) : "memory");
            asm volatile("ld.shared.v2.f32 {%0,%1}, [%2];" : "=f"(u2x), "=f"(u2y) : "r"(dp_r + 32) : "memory");
            if (lane_p == 0) TLD(21, u2x);
            const float st = (((__uint_as_float(s0.x) + __uint_as_float(s0.y)) + (__uint_as_float(s0.z) + __uint_as_float(s0.w))) +
                              ((__uint_as_float(s1.x) + __uint_as_float(s1.y)) + (__uint_as_float(s1.z) + __uint_as_float(s1.w))) + (s2x + s2y)) * (1.0f / 640.0f);
            const float tot = ((__uint_as_float(u0.x) + __uint_as_float(u0.y)) + (__uint_as_float(u0.z) + __uint_as_float(u0.w))) +
                              ((__uint_as_float(u1.x) + __uint_as_float(u1.y)) + (__uint_as_float(u1.z) + __uint_as_float(u1.w))) + (u2x + u2y);
            const float so = __shfl_xor_sync(FULL, st, 1);
            const float cs = __shfl_xor_sync(FULL, tot, 16);
            const float mean = selp(st, so, lane_p & 1), msq = selp(so, st, lane_p & 1);
            const float var = fmaxf(fmaf(-mean, mean, msq), 0.f);
            const float rinv = fast_rcp(bfr(fast_sqrt(bfr(bfr(var) + 1e-5f))));
            const float z = fmaxf(fmaf(-bfr(mean), cs, tot) * rinv, 0.f);
            if (lane_p < 16) asm volatile("st.shared.u16 [%0], %1;" :: "r"(h1_w), "h"((unsigned short)pack_bf(z, 0.f)) : "memory");
            bar_arrive(NB_H1, 352);
        }
        if (f >= NOCT) return;
        mbar_wait(bars + BAR_CLR * 8);
        unsigned ha = ld_w1(hb0);
        bar_sync(NB_DSENT, 352);
        spin_cycles(dly_d);
        {
            uint4 v[7];
#pragma unroll
            for (int j = 0; j < 7; j++) v[j] = ld_w4(d_src + 128 * j);
#pragma unroll 1
            for (int n = 0; n < SPIN_LIMIT; n++) {
                if (!__any_sync(FULL, (ha & tag) == 0)) break;
                ha = ld_w1(hb0);
            }
            float hs = __uint_as_float(ha);
            hs += __shfl_xor_sync(FULL, hs, 8);
            hs += __shfl_xor_sync(FULL, hs, 16);
            const float base = bfr(xcol + bfr(hs));
            float r = 0.f;
#pragma unroll 1
            for (int n = 0; n < SPIN_LIMIT; n++) {
                float t0 = ((__uint_as_float(v[0].x) + __uint_as_float(v[1].x)) + (__uint_as_float(v[2].x) + __uint_as_float(v[3].x))) +
                           ((__uint_as_float(v[4].x) + __uint_as_float(v[5].x)) + __uint_as_float(v[6].x));
                float t1 = ((__uint_as_float(v[0].y) + __uint_as_float(v[1].y)) + (__uint_as_float(v[2].y) + __uint_as_float(v[3].y))) +
                           ((__uint_as_float(v[4].y) + __uint_as_float(v[5].y)) + __uint_as_float(v[6].y));
                float t2 = ((__uint_as_float(v[0].z) + __uint_as_float(v[1].z)) + (__uint_as_float(v[2].z) + __uint_as_float(v[3].z))) +
                           ((__uint_as_float(v[4].z) + __uint_as_float(v[5].z)) + __uint_as_float(v[6].z));
                float t3 = ((__uint_as_float(v[0].w) + __uint_as_float(v[1].w)) + (__uint_as_float(v[2].w) + __uint_as_float(v[3].w))) +
                           ((__uint_as_float(v[4].w) + __uint_as_float(v[5].w)) + __uint_as_float(v[6].w));
                asm volatile("" : "+f"(t0), "+f"(t1), "+f"(t2), "+f"(t3));
                bool miss = false;
#pragma unroll
                for (int j = 0; j < 7; j++)
                    if (bad4(v[j], tag)) { v[j] = ld_w4(d_src + 128 * j); miss = true; }
                const bool again = __any_sync(FULL, miss);
                r = octet_reduce(t0, t1, t2, t3, lane_p);
                if (!again) break;
            }
            if (lane_p < 8) asm volatile("st.global.u16 [%0], %1;" :: "l"(o_dst), "h"((unsigned short)pack_bf(base + bfr(r), 0.f)) : "memory");
            if (lane_p == 0) TL(13);
        }
        if (f == 0 && lane == 0) st_w1(scr + PR_EPOCH * PAIR_W, epoch + 1u);
    }
}

unsigned* g_scr_base = nullptr;
int g_w1_promo = 2;
int g_v_promo = 2;
int g_wo_promo = 2;

}

typedef CUresult (*EncodeTiledFn)(CUtensorMap*, CUtensorMapDataType, cuuint32_t, void*, const cuuint64_t*, const cuuint64_t*,
                                  const cuuint32_t*, const cuuint32_t*, CUtensorMapInterleave, CUtensorMapSwizzle,
                                  CUtensorMapL2promotion, CUtensorMapFloatOOBfill);

extern "C" void kernel_launch(void* const* d_in, const int* in_sizes, int n_in, void* d_out, int out_size) {
    (void)in_sizes; (void)n_in; (void)out_size;
    static EncodeTiledFn encode = nullptr;
    if (!encode) {
        cudaFuncSetAttribute(fk::fused_decode_kernel, cudaFuncAttributeMaxDynamicSharedMemorySize, fk::SMEM_BYTES);
        void* fn = nullptr;
        cudaDriverEntryPointQueryResult qres;
        cudaGetDriverEntryPoint("cuTensorMapEncodeTiled", &fn, cudaEnableDefault, &qres);
        encode = (EncodeTiledFn)fn;
        void* sp = nullptr;
        cudaGetSymbolAddress(&sp, fk::g_scr);
        fk::g_scr_base = (unsigned*)(((uintptr_t)sp + (2u << 20) - 1) & ~(uintptr_t)((2u << 20) - 1));
    }
    CUtensorMap map_v, map_w1, map_wo;
    {
        const cuuint64_t dims[2] = {640, 4096}, strides[1] = {1280};
        const cuuint32_t box[2] = {32, 64}, es[2] = {1, 1};
        encode(&map_wo, CU_TENSOR_MAP_DATA_TYPE_BFLOAT16, 2, d_in[4], dims, strides, box, es, CU_TENSOR_MAP_INTERLEAVE_NONE,
               CU_TENSOR_MAP_SWIZZLE_64B, (CUtensorMapL2promotion)fk::g_wo_promo, CU_TENSOR_MAP_FLOAT_OOB_FILL_NONE);
    }
    {
        const cuuint64_t dims[3] = {64, 32 * 4096, 2}, strides[2] = {256, 128};
        const cuuint32_t box[3] = {64, 16, 2}, es[3] = {1, 1, 1};
        encode(&map_v, CU_TENSOR_MAP_DATA_TYPE_BFLOAT16, 3, d_in[2], dims, strides, box, es, CU_TENSOR_MAP_INTERLEAVE_NONE,
               CU_TENSOR_MAP_SWIZZLE_128B, (CUtensorMapL2promotion)fk::g_v_promo, CU_TENSOR_MAP_FLOAT_OOB_FILL_NONE);
    }
    {
        const cuuint64_t dims[2] = {1728, 640}, strides[1] = {3456};
        const cuuint32_t box[2] = {16, 128}, es[2] = {1, 1};
        encode(&map_w1, CU_TENSOR_MAP_DATA_TYPE_BFLOAT16, 2, d_in[6], dims, strides, box, es, CU_TENSOR_MAP_INTERLEAVE_NONE,
               CU_TENSOR_MAP_SWIZZLE_32B, (CUtensorMapL2promotion)fk::g_w1_promo, CU_TENSOR_MAP_FLOAT_OOB_FILL_NONE);
    }
    fk::fused_decode_kernel<<<fk::NCTA, fk::NTHREADS, fk::SMEM_BYTES>>>(
        (const __nv_bfloat16*)d_in[0], (const __nv_bfloat16*)d_in[3], (const __nv_bfloat16*)d_in[1],
        (const __nv_bfloat16*)d_in[7], (__nv_bfloat16*)d_out, fk::g_scr_base,
        map_v, map_w1, map_wo);
}
```

```cpp
#include <cuda_runtime.h>
#include <cuda.h>
#include <cuda_bf16.h>
#include <stdint.h>
#include <stdlib.h>

namespace fk {

constexpr int NCTA = 128;
constexpr int NFFN = 108;
constexpr int NOCT = 80;
constexpr int NWO = 80;
constexpr int NTHREADS = 384;

constexpr int ROW_PITCH = 1296;
constexpr int SM_K = 0;
constexpr int SM_V = 65536;
constexpr int SM_W1 = 131072;
constexpr int SM_W2 = SM_W1 + 640 * 32;
constexpr int SM_QPART = SM_W2 + 16 * ROW_PITCH;
constexpr int SM_P = SM_QPART + 4096;
constexpr int SM_XN = SM_P + 2048;
constexpr int SM_OPART = SM_XN + 2560;
constexpr int SM_ML = SM_OPART + 1024;
constexpr int SM_QS = SM_ML + 64;
constexpr int SM_HP = SM_QS + 256;
constexpr int SM_DP = SM_HP + 32 * 48;
constexpr int SM_H1 = SM_DP + 34 * 48;
constexpr int SM_OF = SM_H1 + 32;
constexpr int SM_TAG = SM_OF + 16 * 144;
constexpr int SM_BAR = SM_TAG + 32;
constexpr int BAR_K = 0, BAR_V = 16, BAR_WO = 32, BAR_W1 = 40, BAR_W2 = 45, BAR_SIDE = 46, BAR_CLR = 47, BAR_KFREE = 48, BAR_O = 49, NBAR = 50;
constexpr int SMEM_BYTES = SM_BAR + NBAR * 8;

constexpr int SPIN_LIMIT = 1 << 17;
#define NPRE 4

struct Pace {
    int tK;
    int dKV;
    int dWO;
    int dW1;
    int dW2;
    int stag;
    int gap;
    int dlyD;
    int dlyO;
    int nprobe;
    int tP;
    int mode;
    int sV;
};
#define PACE_DEFAULT {1120, 165, 105, 120, 100, 20, 50, 250, 800, 8, 600, 0, 4}

__device__ __align__(4096) unsigned g_scr[1 << 20];
constexpr int PAIR_W = 2048, REP_W = 1024;
constexpr int PR_D = 0;
constexpr int PR_H = 172;
constexpr int PR_O = 84;
constexpr int PR_S = 88;
constexpr int PR_A = 120;
constexpr int PR_SIDE = 136;
constexpr int PR_PROBE = 137;
constexpr int PR_EPOCH = 169;
constexpr int PR_TL = 170;
__device__ __forceinline__ int near_off(int pair, unsigned side) {
    return pair * PAIR_W + (int)((side ^ __popc((2 * pair) & 0xb3)) & 1u) * REP_W;
}
#define TL(i) do {} while (0)
#define TLD(i, v) do {} while (0)
#define TLV(i, v) do {} while (0)

__device__ __forceinline__ unsigned gtime32() {
    unsigned long long t; asm volatile("mov.u64 %0, %globaltimer;" : "=l"(t) :: "memory"); return (unsigned)t;
}
__device__ __forceinline__ uint32_t smem_u32(const void* p) { return (uint32_t)__cvta_generic_to_shared(p); }
__device__ __forceinline__ void mbar_init(uint32_t bar, uint32_t cnt) {
    asm volatile("mbarrier.init.shared::cta.b64 [%0], %1;" :: "r"(bar), "r"(cnt) : "memory");
}
__device__ __forceinline__ void mbar_expect_tx(uint32_t bar, uint32_t bytes) {
    asm volatile("mbarrier.arrive.expect_tx.shared::cta.b64 _, [%0], %1;" :: "r"(bar), "r"(bytes) : "memory");
}
__device__ __forceinline__ void mbar_arrive(uint32_t bar) {
    asm volatile("mbarrier.arrive.shared::cta.b64 _, [%0];" :: "r"(bar) : "memory");
}
__device__ __forceinline__ void mbar_arrive_p(uint32_t bar, unsigned p) {
    asm volatile("{\n.reg .pred p;\nsetp.ne.u32 p, %1, 0;\n@p mbarrier.arrive.shared::cta.b64 _, [%0];\n}" :: "r"(bar), "r"(p) : "memory");
}
__device__ __forceinline__ bool mbar_test(uint32_t bar) {
    uint32_t ok;
    asm volatile("{\n.reg .pred p;\nmbarrier.test_wait.parity.shared::cta.b64 p, [%1], 0;\nselp.u32 %0, 1, 0, p;\n}"
                 : "=r"(ok) : "r"(bar) : "memory");
    return ok != 0;
}
__device__ __forceinline__ bool mbar_try(uint32_t bar) {
    uint32_t ok;
    asm volatile("{\n.reg .pred p;\nmbarrier.try_wait.parity.shared::cta.b64 p, [%1], 0;\nselp.u32 %0, 1, 0, p;\n}"
                 : "=r"(ok) : "r"(bar) : "memory");
    return ok != 0;
}
__device__ __forceinline__ void mbar_wait(uint32_t bar, int lim = SPIN_LIMIT) {
#pragma unroll 1
    for (int n = 0; n < lim; n++) if (mbar_try(bar)) break;
}
__device__ __forceinline__ uint64_t stream_policy() {
    uint64_t p; asm volatile("createpolicy.fractional.L2::evict_first.b64 %0, 1.0;" : "=l"(p)); return p;
}
__device__ __forceinline__ void bulk_g2s(uint32_t dst, const void* src, uint32_t bytes, uint32_t bar, uint64_t pol) {
    asm volatile("cp.async.bulk.shared::cluster.global.mbarrier::complete_tx::bytes.L2::cache_hint [%0], [%1], %2, [%3], %4;"
                 :: "r"(dst), "l"(src), "r"(bytes), "r"(bar), "l"(pol) : "memory");
}
__device__ __forceinline__ void tma2d(uint32_t dst, const CUtensorMap* map, int c0, int c1, uint32_t bar, uint64_t pol) {
    asm volatile("cp.async.bulk.tensor.2d.shared::cluster.global.mbarrier::complete_tx::bytes.L2::cache_hint [%0], [%1, {%3, %4}], [%2], %5;"
                 :: "r"(dst), "l"(map), "r"(bar), "r"(c0), "r"(c1), "l"(pol) : "memory");
}
__device__ __forceinline__ unsigned tagw(float v, unsigned tag) { return (__float_as_uint(v) & ~3u) | tag; }
__device__ __forceinline__ float untag(unsigned w) { return __uint_as_float(w & ~3u); }
__device__ __forceinline__ void st_w1(unsigned* p, unsigned a) {
    asm volatile("st.relaxed.gpu.global.u32 [%0], %1;" :: "l"(p), "r"(a) : "memory");
}
__device__ __forceinline__ void st_w1_p(unsigned* a, unsigned v, unsigned p) {
    asm volatile("{\n.reg .pred p;\nsetp.ne.u32 p, %2, 0;\n@p st.relaxed.gpu.global.u32 [%0], %1;\n}" :: "l"(a), "r"(v), "r"(p) : "memory");
}
__device__ __forceinline__ void st_w4(unsigned* p, uint4 v) {
    asm volatile("st.relaxed.gpu.global.v4.u32 [%0], {%1,%2,%3,%4};" :: "l"(p), "r"(v.x), "r"(v.y), "r"(v.z), "r"(v.w) : "memory");
}
__device__ __forceinline__ unsigned ld_w1(const unsigned* p) {
    unsigned v;
    asm volatile("ld.relaxed.gpu.global.u32 %0, [%1];" : "=r"(v) : "l"(p) : "memory");
    return v;
}
__device__ __forceinline__ uint4 ld_w4(const unsigned* p) {
    uint4 v;
    asm volatile("ld.relaxed.gpu.global.v4.u32 {%0,%1,%2,%3}, [%4];" : "=r"(v.x), "=r"(v.y), "=r"(v.z), "=r"(v.w) : "l"(p) : "memory");
    return v;
}
__device__ __forceinline__ uint2 ld_w2(const unsigned* p) {
    uint2 v;
    asm volatile("ld.relaxed.gpu.global.v2.u32 {%0,%1}, [%2];" : "=r"(v.x), "=r"(v.y) : "l"(p) : "memory");
    return v;
}
__device__ __forceinline__ bool bad2(uint2 v, unsigned tag) { return (v.x & v.y & tag) == 0; }
__device__ __forceinline__ bool bad4(uint4 v, unsigned tag) { return ((v.x & v.y & v.z) & v.w & tag) == 0; }

__device__ __forceinline__ void bar_sync(int id, int n) { __syncwarp(); asm volatile("bar.sync %0, %1;" :: "r"(id), "r"(n) : "memory"); }
__device__ __forceinline__ void bar_arrive(int id, int n) { __syncwarp(); asm volatile("bar.arrive %0, %1;" :: "r"(id), "r"(n) : "memory"); }
template <int ID, int N> __device__ __forceinline__ void bar_sync_p(unsigned p) {
    __syncwarp();
    asm volatile("{\n.reg .pred p;\nsetp.ne.u32 p, %0, 0;\n@p bar.sync %1, %2;\n}" :: "r"(p), "n"(ID), "n"(N) : "memory");
}
template <int ID, int N> __device__ __forceinline__ void bar_arrive_p(unsigned p) {
    __syncwarp();
    asm volatile("{\n.reg .pred p;\nsetp.ne.u32 p, %0, 0;\n@p bar.arrive %1, %2;\n}" :: "r"(p), "n"(ID), "n"(N) : "memory");
}
__device__ __forceinline__ void sts_p(uint32_t a, float v, unsigned p) {
    asm volatile("{\n.reg .pred p;\nsetp.ne.u32 p, %2, 0;\n@p st.shared.f32 [%0], %1;\n}" :: "r"(a), "f"(v), "r"(p) : "memory");
}
__device__ __forceinline__ float bf_lo(unsigned u) { return __uint_as_float(u << 16); }
__device__ __forceinline__ float bf_hi(unsigned u) { return __uint_as_float(u & 0xffff0000u); }
__device__ __forceinline__ unsigned pack_bf(float lo, float hi) {
    unsigned r; asm("cvt.rn.bf16x2.f32 %0, %1, %2;" : "=r"(r) : "f"(hi), "f"(lo)); return r;
}
__device__ __forceinline__ float bfr(float v) { return __uint_as_float(pack_bf(0.f, v)); }
__device__ __forceinline__ float selp(float a, float b, unsigned c) {
    float r; asm("{\n.reg .pred p;\nsetp.ne.u32 p, %3, 0;\nselp.f32 %0, %1, %2, p;\n}" : "=f"(r) : "f"(a), "f"(b), "r"(c)); return r;
}
__device__ __forceinline__ float sel4(float a0, float a1, float a2, float a3, int t) {
    return selp(selp(a3, a2, t & 1), selp(a1, a0, t & 1), t & 2);
}
__device__ __forceinline__ float fast_sqrt(float v) { float r; asm("sqrt.approx.ftz.f32 %0, %1;" : "=f"(r) : "f"(v)); return r; }
__device__ __forceinline__ float fast_rcp(float v) { float r; asm("rcp.approx.ftz.f32 %0, %1;" : "=f"(r) : "f"(v)); return r; }
template <class T> __device__ __forceinline__ T* pin(T* p) { asm volatile("" : "+l"(p)); return p; }
__device__ __forceinline__ void mma16816(float (&c)[4], unsigned a0, unsigned a1, unsigned a2, unsigned a3,
                                         unsigned b0, unsigned b1) {
    asm volatile("mma.sync.aligned.m16n8k16.row.col.f32.bf16.bf16.f32 {%0,%1,%2,%3}, {%4,%5,%6,%7}, {%8,%9}, {%0,%1,%2,%3};"
                 : "+f"(c[0]), "+f"(c[1]), "+f"(c[2]), "+f"(c[3])
                 : "r"(a0), "r"(a1), "r"(a2), "r"(a3), "r"(b0), "r"(b1));
}
__device__ __forceinline__ uint4 ldsm4t(uint32_t addr) {
    uint4 r;
    asm volatile("ldmatrix.sync.aligned.m8n8.x4.trans.shared.b16 {%0,%1,%2,%3}, [%4];"
                 : "=r"(r.x), "=r"(r.y), "=r"(r.z), "=r"(r.w) : "r"(addr) : "memory");
    return r;
}
__device__ __forceinline__ uint4 lds16(uint32_t addr) {
    uint4 r;
    asm volatile("ld.shared.v4.u32 {%0,%1,%2,%3}, [%4];" : "=r"(r.x), "=r"(r.y), "=r"(r.z), "=r"(r.w) : "r"(addr) : "memory");
    return r;
}
__device__ __forceinline__ void wait_until(unsigned t0, int t) {
#pragma unroll 1
    for (int n = 0; n < SPIN_LIMIT; n++) if ((int)(gtime32() - t0) >= t) break;
}
__device__ __forceinline__ void spin_cycles(int n) {
    if (n > 0) { const unsigned c0 = clock(); while ((int)(clock() - c0) < n) {} }
}
__device__ __forceinline__ float octet_reduce(float v0, float v1, float v2, float v3, int lane) {
    const unsigned FULL = 0xffffffffu;
    const unsigned b1 = lane & 2, b2 = lane & 4;
    float k0 = selp(v2, v0, b1), k1 = selp(v3, v1, b1);
    const float s0 = selp(v0, v2, b1), s1 = selp(v1, v3, b1);
    k0 += __shfl_xor_sync(FULL, s0, 2);
    k1 += __shfl_xor_sync(FULL, s1, 2);
    float k = selp(k1, k0, b2);
    const float s = selp(k0, k1, b2);
    k += __shfl_xor_sync(FULL, s, 4);
    k += __shfl_xor_sync(FULL, k, 8);
    k += __shfl_xor_sync(FULL, k, 16);
    return k;
}

constexpr int NB_XN = 1, NB_QPART = 2, NB_Q = 3, NB_OPART = 4, NB_FPART = 5, NB_DSENT = 6, NB_H1 = 7, NB_PROBE = 8, NB_TAG0 = 9, NB_TAG1 = 10, NB_HP = 11;
constexpr int N_XN = NTHREADS - 64;

__global__ void __launch_bounds__(NTHREADS, 1)
fused_decode_kernel(const __nv_bfloat16* __restrict__ x, const __nv_bfloat16* __restrict__ wq,
                    const __nv_bfloat16* __restrict__ kc,
                    const __nv_bfloat16* __restrict__ w2, __nv_bfloat16* __restrict__ out, unsigned* __restrict__ scr,
                    const __grid_constant__ CUtensorMap map_v, const __grid_constant__ CUtensorMap map_w1,
                    const __grid_constant__ CUtensorMap map_wo) {
    constexpr Pace pc = PACE_DEFAULT;
    extern __shared__ __align__(1024) unsigned char smem[];
    const unsigned tstart = gtime32();
    const int tid = threadIdx.x, warp = tid >> 5, lane = tid & 31;
    const int b = blockIdx.x, h = b >> 2, c = b & 3;
    const int cw = warp - 2, ct = tid - 64;

    uint2 xr[5];
    unsigned epoch;
    uint4 wr[10];
    {
        const char* wp = reinterpret_cast<const char*>(wq) + (size_t)(160 * c + (ct >> 4)) * 8192 + h * 256 + (ct & 15) * 16;
        const uint2* xp = reinterpret_cast<const uint2*>(x) + lane;
        asm volatile("{\n.reg .pred p;\nsetp.ne.u32 p, %13, 0;\n@p bra.uni XSKIP;\n"
                     "ld.global.nc.v2.u32 {%0,%1}, [%11];\nld.global.nc.v2.u32 {%2,%3}, [%11+256];\nld.global.nc.v2.u32 {%4,%5}, [%11+512];\n"
                     "ld.global.nc.v2.u32 {%6,%7}, [%11+768];\nld.global.nc.v2.u32 {%8,%9}, [%11+1024];\n"
                     "ld.relaxed.gpu.global.u32 %10, [%12];\nXSKIP:\n}"
                     : "=r"(xr[0].x), "=r"(xr[0].y), "=r"(xr[1].x), "=r"(xr[1].y), "=r"(xr[2].x), "=r"(xr[2].y), "=r"(xr[3].x), "=r"(xr[3].y),
                       "=r"(xr[4].x), "=r"(xr[4].y), "=r"(epoch)
                     : "l"(xp), "l"(scr + PR_EPOCH * PAIR_W), "r"(warp) : "memory");
        asm volatile("{\n.reg .pred p;\nsetp.ge.u32 p, %41, 8;\n@p bra.uni WSKIP;\n"
                     "ld.global.nc.L1::no_allocate.v4.u32 {%0,%1,%2,%3}, [%40];\n"
                     "ld.global.nc.L1::no_allocate.v4.u32 {%4,%5,%6,%7}, [%40+131072];\n"
                     "ld.global.nc.L1::no_allocate.v4.u32 {%8,%9,%10,%11}, [%40+262144];\n"
                     "ld.global.nc.L1::no_allocate.v4.u32 {%12,%13,%14,%15}, [%40+393216];\n"
                     "ld.global.nc.L1::no_allocate.v4.u32 {%16,%17,%18,%19}, [%40+524288];\n"
                     "ld.global.nc.L1::no_allocate.v4.u32 {%20,%21,%22,%23}, [%40+655360];\n"
                     "ld.global.nc.L1::no_allocate.v4.u32 {%24,%25,%26,%27}, [%40+786432];\n"
                     "ld.global.nc.L1::no_allocate.v4.u32 {%28,%29,%30,%31}, [%40+917504];\n"
                     "ld.global.nc.L1::no_allocate.v4.u32 {%32,%33,%34,%35}, [%40+1048576];\n"
                     "ld.global.nc.L1::no_allocate.v4.u32 {%36,%37,%38,%39}, [%40+1179648];\n"
                     "WSKIP:\n}"
                     : "=r"(wr[0].x), "=r"(wr[0].y), "=r"(wr[0].z), "=r"(wr[0].w), "=r"(wr[1].x), "=r"(wr[1].y), "=r"(wr[1].z), "=r"(wr[1].w),
                       "=r"(wr[2].x), "=r"(wr[2].y), "=r"(wr[2].z), "=r"(wr[2].w), "=r"(wr[3].x), "=r"(wr[3].y), "=r"(wr[3].z), "=r"(wr[3].w),
                       "=r"(wr[4].x), "=r"(wr[4].y), "=r"(wr[4].z), "=r"(wr[4].w), "=r"(wr[5].x), "=r"(wr[5].y), "=r"(wr[5].z), "=r"(wr[5].w),
                       "=r"(wr[6].x), "=r"(wr[6].y), "=r"(wr[6].z), "=r"(wr[6].w), "=r"(wr[7].x), "=r"(wr[7].y), "=r"(wr[7].z), "=r"(wr[7].w),
                       "=r"(wr[8].x), "=r"(wr[8].y), "=r"(wr[8].z), "=r"(wr[8].w), "=r"(wr[9].x), "=r"(wr[9].y), "=r"(wr[9].z), "=r"(wr[9].w)
                     : "l"(wp), "r"(cw));
    }
    if (ct == 0) TL(15);

    const uint32_t sb = smem_u32(smem);
    const uint32_t bars = sb + SM_BAR;
    const int g = lane >> 2, t = lane & 3;
    const unsigned FULL = 0xffffffffu;
    volatile unsigned* const misc = reinterpret_cast<volatile unsigned*>(smem + SM_TAG);
    const int f = (b >= NWO) ? b - NWO : b + (NCTA - NWO);

    if ((unsigned)cw < 10u) {
        const int mi = lane >> 3, ri = lane & 7;
        unsigned tag, side, sd0, sd1;
        const int oct = 2 * (4 * cw + t);
        const unsigned xpair = __ldg(reinterpret_cast<const unsigned*>(x) + ct);
        if (cw < 8) {
            bar_sync(NB_XN, N_XN);
            tag = misc[0];
            unsigned* const s_dst = scr + (PR_S + h) * PAIR_W + c * 256 + (cw + 8 * (t >> 1)) * 16 + 8 * (t & 1) + g;
            st_w1(s_dst, 0u); st_w1(s_dst + REP_W, 0u);
            {
                const float* xn = reinterpret_cast<const float*>(smem + SM_XN) + 160 * c + (ct >> 4);
                float acc[8];
#pragma unroll
                for (int j = 0; j < 8; j++) acc[j] = 0.f;
#pragma unroll
                for (int i = 0; i < 10; i++) {
                    const float xv = xn[16 * i];
                    acc[0] = fmaf(xv, bf_lo(wr[i].x), acc[0]); acc[1] = fmaf(xv, bf_hi(wr[i].x), acc[1]);
                    acc[2] = fmaf(xv, bf_lo(wr[i].y), acc[2]); acc[3] = fmaf(xv, bf_hi(wr[i].y), acc[3]);
                    acc[4] = fmaf(xv, bf_lo(wr[i].z), acc[4]); acc[5] = fmaf(xv, bf_hi(wr[i].z), acc[5]);
                    acc[6] = fmaf(xv, bf_lo(wr[i].w), acc[6]); acc[7] = fmaf(xv, bf_hi(wr[i].w), acc[7]);
                }
#pragma unroll
                for (int j = 0; j < 8; j++) acc[j] += __shfl_xor_sync(FULL, acc[j], 16);
                if (lane < 16) {
                    float4* qp = reinterpret_cast<float4*>(smem + SM_QPART + cw * 512 + lane * 32);
                    qp[0] = make_float4(acc[0], acc[1], acc[2], acc[3]);
                    qp[1] = make_float4(acc[4], acc[5], acc[6], acc[7]);
                }
            }
            bar_arrive(NB_QPART, 288);
            if (pc.mode == 1) return;
            bar_sync(NB_Q, 288);
            uint4 qf[4];
#pragma unroll
            for (int j = 0; j < 4; j++) qf[j] = lds16(sb + SM_QS + 16 * (t + 4 * (j ^ (g & 1))));
            float mys = 0.f;
#pragma unroll 1
            for (int tile = 0; tile < 2; tile++) {
                const int ch = cw + 8 * tile;
                mbar_wait(bars + (BAR_K + ch) * 8);
                const uint32_t kb = sb + SM_K + ch * 4096 + g * 256 + t * 16;
                float cA[4] = {0.f, 0.f, 0.f, 0.f}, cB[4] = {0.f, 0.f, 0.f, 0.f};
#pragma unroll
                for (int j = 0; j < 4; j++) {
                    const uint32_t a = kb + 64 * (j ^ (g & 1));
                    const uint4 ra = lds16(a), rb = lds16(a + 2048);
                    mma16816(cA, ra.x, rb.x, ra.y, rb.y, qf[j].x, qf[j].y);
                    mma16816(cB, ra.z, rb.z, ra.w, rb.w, qf[j].z, qf[j].w);
                }
                const float s0 = selp(cA[1] + cB[1], cA[0] + cB[0], g & 1);
                const float s1 = selp(cA[3] + cB[3], cA[2] + cB[2], g & 1);
                mys = selp(selp(s1, s0, t & 1), mys, (t >> 1) == tile);
            }
            __syncwarp();
            if (lane == 0) mbar_arrive(bars + BAR_KFREE * 8);
            mys = bfr(bfr(mys) * 0.08838834764831845f);
            st_w1(s_dst, __float_as_uint(mys) | tag);
            st_w1(s_dst + REP_W, __float_as_uint(mys) | tag);
            if (ct == 224) TL(3);
            {
                mbar_wait(bars + (BAR_V + pc.sV) * 8);
                mbar_wait(bars + BAR_SIDE * 8);
                const unsigned* ps = scr + near_off(PR_S + h, misc[1]) + (cw + 8 * (lane >> 4)) * 64 + 4 * (lane & 15);
                uint4 v = ld_w4(ps);
#pragma unroll 1
                for (int n = 0; n < SPIN_LIMIT; n++) {
                    if (!__any_sync(FULL, bad4(v, tag))) break;
                    __nanosleep(50);
                    v = ld_w4(ps);
                }
                if (ct == 224) TL(28);
                const float e0 = untag(v.x), e1 = untag(v.y), e2 = untag(v.z), e3 = untag(v.w);
                float m = fmaxf(fmaxf(e0, e1), fmaxf(e2, e3));
#pragma unroll
                for (int o = 16; o; o >>= 1) m = fmaxf(m, __shfl_xor_sync(FULL, m, o));
                const unsigned p01 = pack_bf(__expf(e0 - m), __expf(e1 - m)), p23 = pack_bf(__expf(e2 - m), __expf(e3 - m));
                reinterpret_cast<uint2*>(smem + SM_P)[cw * 32 + lane] = make_uint2(p01, p23);
                float l = (bf_lo(p01) + bf_hi(p01)) + (bf_lo(p23) + bf_hi(p23));
#pragma unroll
                for (int o = 16; o; o >>= 1) l += __shfl_xor_sync(FULL, l, o);
                if (lane == 0) reinterpret_cast<float2*>(smem + SM_ML)[cw] = make_float2(m, l);
                __syncwarp();
                if (ct == 224) TL(5);
            }
            float o0[4] = {0.f, 0.f, 0.f, 0.f}, o1[4] = {0.f, 0.f, 0.f, 0.f};
            const int vrow = (mi >> 1) * 8 + ri;
            const uint32_t va0 = vrow * 64 + (((mi & 1) ^ ((ri >> 1) & 3)) * 16);
            const uint32_t va1 = vrow * 64 + (((2 + (mi & 1)) ^ ((ri >> 1) & 3)) * 16);
#pragma unroll 1
            for (int tile = 0; tile < 2; tile++) {
                const int ch = cw + 8 * tile;
                const unsigned* pp = reinterpret_cast<const unsigned*>(smem + SM_P) + cw * 64 + tile * 32 + t;
                unsigned pf[8];
#pragma unroll
                for (int s = 0; s < 8; s++) pf[s] = pp[4 * s];
                mbar_wait(bars + (BAR_V + ch) * 8);
                const uint32_t vb = sb + SM_V + ch * 4096;
#pragma unroll
                for (int s = 0; s < 4; s++) {
                    const uint4 a0 = ldsm4t(vb + s * 1024 + va0), a1 = ldsm4t(vb + s * 1024 + va1);
                    mma16816(o0, a0.x, a0.y, a0.z, a0.w, pf[2 * s], pf[2 * s + 1]);
                    mma16816(o1, a1.x, a1.y, a1.z, a1.w, pf[2 * s], pf[2 * s + 1]);
                }
            }
            reinterpret_cast<float*>(smem + SM_OPART)[cw * 32 + 8 * t + g] = sel4(o0[0], o0[2], o1[0], o1[2], t);
            bar_arrive(NB_OPART, 288);
            side = misc[1];
            sd0 = ld_w1(scr + near_off(PR_SIDE, side) + oct * 8); sd1 = ld_w1(scr + near_off(PR_SIDE, side) + oct * 8 + 8);
            if (b < NWO) {
                const int ks = cw >> 1;
                const uint32_t ab = sb + SM_K + (cw & 1) * 4096 + (16 * ks + (mi >> 1) * 8 + ri) * 64;
                const uint32_t ab0 = ab + (((mi & 1) ^ ((ri >> 1) & 3)) * 16), ab1 = ab + (((2 + (mi & 1)) ^ ((ri >> 1) & 3)) * 16);
                uint4 a[2 * NPRE];
#pragma unroll
                for (int i = 0; i < NPRE; i++) {
                    mbar_wait(bars + (BAR_WO + i) * 8);
                    a[2 * i] = ldsm4t(ab0 + i * 8192); a[2 * i + 1] = ldsm4t(ab1 + i * 8192);
                }
                mbar_wait(bars + BAR_O * 8);
                uint4 bf[4];
#pragma unroll
                for (int i = 0; i < 4; i++) bf[i] = lds16(sb + SM_OF + (ks * 4 + t) * 144 + (cw & 1) * 64 + i * 16);
                float cc[4][4];
#pragma unroll
                for (int i = 0; i < 4; i++) cc[i][0] = cc[i][1] = cc[i][2] = cc[i][3] = 0.f;
#pragma unroll
                for (int i = 0; i < 8; i++) {
                    uint4 a0, a1;
                    if (i < NPRE) { a0 = a[2 * i]; a1 = a[2 * i + 1]; }
                    else {
                        mbar_wait(bars + (BAR_WO + i) * 8);
                        a0 = ldsm4t(ab0 + i * 8192); a1 = ldsm4t(ab1 + i * 8192);
                    }
                    const unsigned b0 = (i & 1) ? bf[i >> 1].z : bf[i >> 1].x, b1 = (i & 1) ? bf[i >> 1].w : bf[i >> 1].y;
                    mma16816(cc[2 * (i & 1)], a0.x, a0.y, a0.z, a0.w, b0, b1);
                    mma16816(cc[2 * (i & 1) + 1], a1.x, a1.y, a1.z, a1.w, b0, b1);
                }
                sts_p(sb + SM_HP + ((8 * t + g) * 12 + cw) * 4,
                      sel4(cc[0][0] + cc[2][0], cc[0][2] + cc[2][2], cc[1][0] + cc[3][0], cc[1][2] + cc[3][2], t), 1u);
                bar_arrive(NB_HP, 288);
                if (ct == 0) TL(6);
            }
        } else {
            unsigned* const probe = scr + near_off(PR_PROBE + (b >> 2), cw & 1) + (b & 3) * 256;
            st_w1(probe + (lane >> 3) * 32 + (lane & 7), 0u);
            st_w1(probe + 128 + (lane >> 3) * 32 + (lane & 7), 0u);
            if (cw == 8 && lane == 0) misc[2] = 0u;
            wait_until(tstart, pc.tP);
            bar_sync(NB_PROBE, 64);
            unsigned v = 0;
#pragma unroll 1
            for (int i = 0; i < pc.nprobe; i++) v = ld_w1(probe + i * 32 + v);
            unsigned won = 0;
            if (lane == 0) won = (atomicExch(reinterpret_cast<unsigned*>(smem + SM_TAG) + 2, 1u + v) == 0u);
            won = __shfl_sync(FULL, won, 0);
            if (cw & 1) bar_sync(NB_TAG1, 64); else bar_sync(NB_TAG0, 64);
            tag = misc[0];
            if (pc.mode == 1) return;
            if (won) {
                const unsigned sd = cw & 1;
                if (lane == 0) {
                    misc[1] = sd;
                    mbar_arrive(bars + BAR_SIDE * 8);
                    TL(23);
                }
                if (f < NOCT) {
                    unsigned* i1 = scr + near_off(PR_D + f, sd) + 4 * lane;
#pragma unroll
                    for (int j = 0; j < 7; j++) {
                        const unsigned z = (j * 16 + (lane >> 1) >= NFFN) ? tag : 0u;
                        st_w4(i1 + 128 * j, make_uint4(z, z, z, z));
                    }
                    asm volatile("fence.acq_rel.gpu;" ::: "memory");
                    __syncwarp();
                    if (lane < 16) st_w1(scr + PR_SIDE * PAIR_W + (lane >> 3) * REP_W + f * 8 + (lane & 7), (sd << 2) | tag);
                    if (lane == 0) { mbar_arrive(bars + BAR_CLR * 8); TL(30); }
                }
            }
            mbar_wait(bars + (BAR_V + 15) * 8);
            mbar_wait(bars + BAR_SIDE * 8);
            side = misc[1];
            sd0 = ld_w1(scr + near_off(PR_SIDE, side) + oct * 8); sd1 = ld_w1(scr + near_off(PR_SIDE, side) + oct * 8 + 8);
            if (b < NWO) {
                const unsigned* po = scr + near_off(PR_O + b / 20, side) + (cw & 1) * 512 + 4 * lane;
                unsigned* of = reinterpret_cast<unsigned*>(smem + SM_OF) + (((lane >> 2) & 3) * 4 + 2 * (lane & 1)) * 36 +
                               (lane >> 4) * 16 + 8 * (cw & 1) + ((lane >> 1) & 1);
                spin_cycles(pc.dlyO);
                uint4 ov[4];
#pragma unroll
                for (int q = 0; q < 4; q++) ov[q] = ld_w4(po + 128 * q);
#pragma unroll 1
                for (int n = 0; n < SPIN_LIMIT; n++) {
                    bool miss = false;
#pragma unroll
                    for (int q = 0; q < 4; q++) if (bad4(ov[q], tag)) { ov[q] = ld_w4(po + 128 * q); miss = true; }
                    if (!__any_sync(FULL, miss)) break;
                }
#pragma unroll
                for (int q = 0; q < 4; q++) {
                    of[2 * q] = __byte_perm(ov[q].x, ov[q].y, 0x7632);
                    of[2 * q + 36] = __byte_perm(ov[q].z, ov[q].w, 0x7632);
                }
                __syncwarp();
                if (lane == 0) { mbar_arrive(bars + BAR_O * 8); if (cw == 8) TL(29); }
            }
        }
        if (f >= NFFN) return;

        const unsigned* const sd_src = scr + near_off(PR_SIDE, side) + oct * 8;
        const unsigned* const h_src0 = pin(scr + near_off(PR_H + 4 * (b & 1), side) + 2 * ct);
        const unsigned* const h_src1 = pin(scr + near_off(PR_H + 4 * (b & 1) + 1, side) + 2 * ct);
        const unsigned* const h_src2 = pin(scr + near_off(PR_H + 4 * (b & 1) + 2, side) + 2 * ct);
        const unsigned* const h_src3 = pin(scr + near_off(PR_H + 4 * (b & 1) + 3, side) + 2 * ct);
#pragma unroll 1
        for (int n = 0; n < SPIN_LIMIT; n++) {
            if (!__any_sync(FULL, (sd0 & sd1 & tag) == 0)) break;
            __nanosleep(100);
            sd0 = ld_w1(sd_src); sd1 = ld_w1(sd_src + 8);
        }
        unsigned* const d_a = pin(scr + near_off(PR_D + oct, sd0 >> 2) + f * 8 + g);
        unsigned* const d_b = pin(scr + near_off(PR_D + oct + 1, sd1 >> 2) + f * 8 + g);
        uint32_t dp_w = sb + SM_DP + ((g + 8 * t) * 12 + cw) * 4;
        uint32_t st_w = sb + SM_DP + ((32 + lane) * 12 + cw) * 4;
        uint32_t w2_r = sb + SM_W2 + ((mi >> 1) * 8 + ri) * ROW_PITCH + cw * 128 + (mi & 1) * 16;
        uint32_t w1_r = sb + SM_W1 + (64 * cw + (mi >> 1) * 8 + ri) * 32 + (((mi & 1) ^ (ri >> 2)) * 16);
        uint32_t w1_bar = bars + (BAR_W1 + (cw >> 1)) * 8;
        asm volatile("" : "+r"(dp_w), "+r"(st_w), "+r"(w2_r), "+r"(w1_r), "+r"(w1_bar));
        mbar_wait(bars + ((b < NWO) ? BAR_WO + 7 : BAR_W1) * 8);
        uint2 h0 = ld_w2(h_src0), h1 = ld_w2(h_src1), h2 = ld_w2(h_src2), h3 = ld_w2(h_src3);
        uint4 a[4];
        bool w1_in = false;
#pragma unroll 1
        for (int n = 0; n < SPIN_LIMIT; n++) {
            if (!w1_in && mbar_test(w1_bar)) {
                w1_in = true;
#pragma unroll
                for (int s = 0; s < 4; s++) a[s] = ldsm4t(w1_r + s * 512);
            }
            bool miss = false;
            if (bad2(h0, tag)) { h0 = ld_w2(h_src0); miss = true; }
            if (bad2(h1, tag)) { h1 = ld_w2(h_src1); miss = true; }
            if (bad2(h2, tag)) { h2 = ld_w2(h_src2); miss = true; }
            if (bad2(h3, tag)) { h3 = ld_w2(h_src3); miss = true; }
            if (!__any_sync(FULL, miss)) break;
        }
        const unsigned att = pack_bf((__uint_as_float(h0.x) + __uint_as_float(h1.x)) + (__uint_as_float(h2.x) + __uint_as_float(h3.x)),
                                     (__uint_as_float(h0.y) + __uint_as_float(h1.y)) + (__uint_as_float(h2.y) + __uint_as_float(h3.y)));
        const unsigned hpair = pack_bf(bf_lo(xpair) + bf_lo(att), bf_hi(xpair) + bf_hi(att));
        if (ct == 0) TL(8);
        unsigned hf[8];
#pragma unroll
        for (int s = 0; s < 8; s++) hf[s] = __shfl_sync(FULL, hpair, 4 * s + t);
        {
            float sA[4] = {0.f, 0.f, 0.f, 0.f}, sB[4] = {0.f, 0.f, 0.f, 0.f};
#pragma unroll
            for (int s = 0; s < 4; s += 2) {
                mma16816(sA, hf[2 * s], 0x3F803F80u, hf[2 * s + 1], 0x3F803F80u, hf[2 * s], hf[2 * s + 1]);
                mma16816(sB, hf[2 * s + 2], 0x3F803F80u, hf[2 * s + 3], 0x3F803F80u, hf[2 * s + 2], hf[2 * s + 3]);
            }
            if (!w1_in) {
                mbar_wait(w1_bar);
#pragma unroll
                for (int s = 0; s < 4; s++) a[s] = ldsm4t(w1_r + s * 512);
            }
            float dA[4] = {0.f, 0.f, 0.f, 0.f}, dB[4] = {0.f, 0.f, 0.f, 0.f};
#pragma unroll
            for (int s = 0; s < 8; s++) hf[s] = (g < 4) ? hf[s] : 0x3F803F80u;
#pragma unroll
            for (int s = 0; s < 4; s += 2) {
                mma16816(dA, a[s].x, a[s].y, a[s].z, a[s].w, hf[2 * s], hf[2 * s + 1]);
                mma16816(dB, a[s + 1].x, a[s + 1].y, a[s + 1].z, a[s + 1].w, hf[2 * s + 2], hf[2 * s + 3]);
            }
            sts_p(st_w, selp(sA[2] + sB[2], sA[0] + sB[0], lane), lane < 2);
            sts_p(dp_w, selp(dA[2] + dB[2], dA[0] + dB[0], t & 1), 1u);
        }
        if (ct == 0) TL(7);
        bar_arrive(NB_FPART, 352);
        uint4 w[4];
        mbar_wait(bars + BAR_W2 * 8);
#pragma unroll
        for (int j = 0; j < 4; j++) w[j] = ldsm4t(w2_r + j * 32);
        bar_sync(NB_H1, 352);
        unsigned b0, b1;
        asm volatile("ld.shared.u32 %0, [%1];" : "=r"(b0) : "r"(sb + SM_H1 + 4 * t) : "memory");
        asm volatile("ld.shared.u32 %0, [%1];" : "=r"(b1) : "r"(sb + SM_H1 + 16 + 4 * t) : "memory");
        float y[4][4];
#pragma unroll
        for (int j = 0; j < 4; j++) {
            y[j][0] = y[j][1] = y[j][2] = y[j][3] = 0.f;
            mma16816(y[j], w[j].x, w[j].y, w[j].z, w[j].w, b0, b1);
        }
        st_w1(d_a, tagw(sel4(y[0][0], y[1][0], y[2][0], y[3][0], t), tag));
        st_w1(d_b, tagw(sel4(y[0][2], y[1][2], y[2][2], y[3][2], t), tag));
        if (ct == 0) TL(9);
        if (f < NOCT) bar_arrive(NB_DSENT, 352);
    } else if (warp == 1) {
        const unsigned t0 = tstart + (unsigned)((h & 7) * pc.stag);
        if (lane == 0) {
            TLV(0, tstart);
#pragma unroll
            for (int i = 0; i < BAR_KFREE; i++) mbar_init(bars + i * 8, 1);
            mbar_init(bars + BAR_KFREE * 8, 8);
            mbar_init(bars + BAR_O * 8, 2);
            asm volatile("fence.mbarrier_init.release.cluster;" ::: "memory");
            asm volatile("prefetch.tensormap [%0];" :: "l"(&map_v) : "memory");
            asm volatile("prefetch.tensormap [%0];" :: "l"(&map_w1) : "memory");
            asm volatile("prefetch.tensormap [%0];" :: "l"(&map_wo) : "memory");
        }
        bar_arrive(NB_XN, N_XN);
        if (lane == 0) {
            int tt = pc.tK;
            const uint64_t pol = stream_policy();
            const char* ks = reinterpret_cast<const char*>(kc) + (size_t)h * 1048576 + 786432 + c * 65536;
#pragma unroll 1
            for (int ii = 0; ii < 16; ii++) {
                const int i = ii;
                wait_until(t0, tt); tt += pc.dKV;
                mbar_expect_tx(bars + (BAR_K + i) * 8, 4096);
                bulk_g2s(sb + SM_K + i * 4096, ks + i * 4096, 4096, bars + (BAR_K + i) * 8, pol);
            }
#pragma unroll 1
            for (int ii = 0; ii < 16; ii++) {
                const int i = ii;
                wait_until(t0, tt); tt += pc.dKV;
                mbar_expect_tx(bars + (BAR_V + i) * 8, 4096);
                tma2d(sb + SM_V + i * 4096, &map_v, 32 * c, h * 4096 + 3072 + 64 * i, bars + (BAR_V + i) * 8, pol);
            }
            if (b < NWO) {
                const int c0 = 32 * (b % 20), r0 = 1024 * (b / 20);
                if (pc.mode != 1) mbar_wait(bars + BAR_KFREE * 8);
#pragma unroll 1
                for (int i = 0; i < 16; i++) {
                    wait_until(t0, tt + i * pc.dWO);
                    if (!(i & 1)) mbar_expect_tx(bars + (BAR_WO + (i >> 1)) * 8, 8192);
                    tma2d(sb + SM_K + i * 4096, &map_wo, c0, r0 + 64 * i, bars + (BAR_WO + (i >> 1)) * 8, pol);
                }
            }
            tt += 16 * pc.dWO + pc.gap;
            if (f < NFFN) {
#pragma unroll 1
                for (int j = 0; j < 5; j++) {
                    wait_until(t0, tt); tt += pc.dW1;
                    mbar_expect_tx(bars + (BAR_W1 + j) * 8, 4096);
                    tma2d(sb + SM_W1 + j * 4096, &map_w1, 16 * f, 128 * j, bars + (BAR_W1 + j) * 8, pol);
                }
                const char* w2s = reinterpret_cast<const char*>(w2) + (size_t)f * 16 * 1280;
                mbar_expect_tx(bars + BAR_W2 * 8, 16 * 1280);
#pragma unroll 1
                for (int j = 0; j < 4; j++) {
                    wait_until(t0, tt); tt += pc.dW2;
#pragma unroll
                    for (int i = 0; i < 4; i++) {
                        const int r = j * 4 + i;
                        bulk_g2s(sb + SM_W2 + r * ROW_PITCH, w2s + r * 1280, 1280, bars + BAR_W2 * 8, pol);
                    }
                }
                TL(10);
            }
            if (pc.mode == 1) {
                for (int i = 0; i < BAR_SIDE; i++)
                    if (i < BAR_WO || (i < BAR_W1 ? b < NWO : f < NFFN)) mbar_wait(bars + i * 8);
            }
        }
    } else {
        const int col = 8 * f + 4 * (lane & 1) + (lane & 2) + ((lane >> 2) & 1);
        float xcol = 0.f;
        if (f < NOCT) xcol = __bfloat162float(x[col]);
        {
            float s = 0.f;
#pragma unroll
            for (int j = 0; j < 5; j++) s += (bf_lo(xr[j].x) + bf_hi(xr[j].x)) + (bf_lo(xr[j].y) + bf_hi(xr[j].y));
#pragma unroll
            for (int o = 16; o; o >>= 1) s += __shfl_xor_sync(FULL, s, o);
            const float mean = s * (1.0f / 640.0f);
            float v = 0.f;
#pragma unroll
            for (int j = 0; j < 5; j++) {
                float d0 = bf_lo(xr[j].x) - mean, d1 = bf_hi(xr[j].x) - mean, d2 = bf_lo(xr[j].y) - mean, d3 = bf_hi(xr[j].y) - mean;
                v += (d0 * d0 + d1 * d1) + (d2 * d2 + d3 * d3);
            }
#pragma unroll
            for (int o = 16; o; o >>= 1) v += __shfl_xor_sync(FULL, v, o);
            const float mb = bfr(mean);
            const float rb = __frcp_rn(bfr(__fsqrt_rn(bfr(bfr(v * (1.0f / 640.0f)) + 1e-5f))));
            float4* xn = reinterpret_cast<float4*>(smem + SM_XN);
#pragma unroll
            for (int j = 0; j < 5; j++) {
                float4 o;
                o.x = bfr(bfr(bf_lo(xr[j].x) - mb) * rb); o.y = bfr(bfr(bf_hi(xr[j].x) - mb) * rb);
                o.z = bfr(bfr(bf_lo(xr[j].y) - mb) * rb); o.w = bfr(bfr(bf_hi(xr[j].y) - mb) * rb);
                xn[j * 32 + lane] = o;
            }
        }
        const unsigned tag = 1u + (epoch & 1u);
        if (lane == 0) misc[0] = tag;
        if (lane == 0) TL(22);
        bar_sync(NB_XN, N_XN);
        bar_arrive(NB_TAG0, 64);
        bar_arrive(NB_TAG1, 64);
        unsigned* const a_dst = scr + (PR_A + (h >> 1)) * PAIR_W + (b & 7) * 128 + 4 * lane;
        unsigned* const h_dst = pin(scr + (PR_H + b / 20) * PAIR_W + 32 * (b % 20) + lane);
        unsigned* const o_msg = pin(scr + (PR_O + (b >> 5)) * PAIR_W + (b & 31) * 32 + lane);
        st_w1(o_msg, 0u); st_w1(o_msg + REP_W, 0u);
        st_w4(a_dst, make_uint4(0u, 0u, 0u, 0u));
        st_w4(a_dst + REP_W, make_uint4(0u, 0u, 0u, 0u));
        if (b < NWO) { st_w1(h_dst, 0u); st_w1(h_dst + REP_W, 0u); st_w1(h_dst + 4 * PAIR_W, 0u); st_w1(h_dst + 4 * PAIR_W + REP_W, 0u); }
        bar_sync(NB_QPART, 288);
        {
            const float4* qp = reinterpret_cast<const float4*>(smem + SM_QPART) + lane;
            float4 s = qp[0];
            if (lane == 0) TLD(1, s.x);
#pragma unroll
            for (int w = 1; w < 8; w++) { const float4 u = qp[w * 32]; s.x += u.x; s.y += u.y; s.z += u.z; s.w += u.w; }
            const uint4 mine = make_uint4(tagw(s.x, tag), tagw(s.y, tag), tagw(s.z, tag), tagw(s.w, tag));
            st_w4(a_dst, mine);
            st_w4(a_dst + REP_W, mine);
            if (pc.mode == 1) return;
            mbar_wait(bars + BAR_SIDE * 8);
            const unsigned* pa = scr + near_off(PR_A + (h >> 1), misc[1]) + (h & 1) * 512 + 4 * lane;
            uint4 v[4];
#pragma unroll 1
            for (int n = 0; n < SPIN_LIMIT; n++) {
#pragma unroll
                for (int cc = 0; cc < 4; cc++) v[cc] = (cc == c) ? mine : ld_w4(pa + cc * 128);
                if (!__any_sync(FULL, bad4(v[0], tag) | bad4(v[1], tag) | bad4(v[2], tag) | bad4(v[3], tag))) break;
                __nanosleep(50);
            }
            const float q0 = ((untag(v[0].x) + untag(v[1].x)) + untag(v[2].x)) + untag(v[3].x);
            const float q1 = ((untag(v[0].y) + untag(v[1].y)) + untag(v[2].y)) + untag(v[3].y);
            const float q2 = ((untag(v[0].z) + untag(v[1].z)) + untag(v[2].z)) + untag(v[3].z);
            const float q3 = ((untag(v[0].w) + untag(v[1].w)) + untag(v[2].w)) + untag(v[3].w);
            reinterpret_cast<uint2*>(smem + SM_QS)[lane] = make_uint2(pack_bf(q0, q1), pack_bf(q2, q3));
        }
        bar_arrive(NB_Q, 288);
        if (lane == 0) TL(2);
        bar_sync(NB_OPART, 288);
        {
            const float* op = reinterpret_cast<const float*>(smem + SM_OPART) + lane;
            const float4* ml = reinterpret_cast<const float4*>(smem + SM_ML);
            const float4 e0 = ml[0], e1 = ml[1], e2 = ml[2], e3 = ml[3];
            const float M = fmaxf(fmaxf(fmaxf(e0.x, e0.z), fmaxf(e1.x, e1.z)), fmaxf(fmaxf(e2.x, e2.z), fmaxf(e3.x, e3.z)));
            const float f0 = __expf(e0.x - M), f1 = __expf(e0.z - M), f2 = __expf(e1.x - M), f3 = __expf(e1.z - M);
            const float f4 = __expf(e2.x - M), f5 = __expf(e2.z - M), f6 = __expf(e3.x - M), f7 = __expf(e3.z - M);
            const float l = ((f0 * e0.y + f1 * e0.w) + (f2 * e1.y + f3 * e1.w)) + ((f4 * e2.y + f5 * e2.w) + (f6 * e3.y + f7 * e3.w));
            float o = ((f0 * op[0] + f1 * op[32]) + (f2 * op[64] + f3 * op[96])) + ((f4 * op[128] + f5 * op[160]) + (f6 * op[192] + f7 * op[224]));
            const unsigned ow = __float_as_uint(bfr(o * fast_rcp(l))) | tag;
            st_w1(o_msg, ow); st_w1(o_msg + REP_W, ow);
            if (lane == 0) TL(4);
        }
        const unsigned side = misc[1];
        const unsigned* const d_src = pin(scr + near_off(PR_D + f, side) + 4 * lane);
        const unsigned* const hb0 = pin(scr + near_off(PR_H + 4 * (b & 1) + (lane >> 3), side) + col);
        __nv_bfloat16* const o_dst = pin(out + col);
        int lane_p = lane, dly_d = pc.dlyD;
        uint32_t hp_r = sb + SM_HP + lane * 48;
        asm volatile("" : "+r"(lane_p), "+r"(dly_d), "+r"(hp_r));
        if (b < NWO) {
            bar_sync(NB_HP, 288);
            const uint4 u0 = lds16(hp_r), u1 = lds16(hp_r + 16);
            const unsigned hw = tagw(((__uint_as_float(u0.x) + __uint_as_float(u0.y)) + (__uint_as_float(u0.z) + __uint_as_float(u0.w))) +
                                     ((__uint_as_float(u1.x) + __uint_as_float(u1.y)) + (__uint_as_float(u1.z) + __uint_as_float(u1.w))), tag);
            st_w1(h_dst, hw); st_w1(h_dst + REP_W, hw); st_w1(h_dst + 4 * PAIR_W, hw); st_w1(h_dst + 4 * PAIR_W + REP_W, hw);
            if (lane_p == 0) TL(12);
        }
        if (f >= NFFN) return;
        {
            uint32_t dp_r = sb + SM_DP + lane * 48, st_r = sb + SM_DP + (32 + (lane & 1)) * 48, h1_w = sb + SM_H1 + 2 * lane;
            asm volatile("" : "+r"(dp_r), "+r"(st_r), "+r"(h1_w));
            bar_sync(NB_FPART, 352);
            const uint4 s0 = lds16(st_r), s1 = lds16(st_r + 16), u0 = lds16(dp_r), u1 = lds16(dp_r + 16);
            float s2x, s2y, u2x, u2y;
            asm volatile("ld.shared.v2.f32 {%0,%1}, [%2];" : "=f"(s2x), "=f"(s2y) : "r"(st_r + 32) : "memory");
            asm volatile("ld.shared.v2.f32 {%0,%1}, [%2];" : "=f"(u2x), "=f"(u2y) : "r"(dp_r + 32) : "memory");
            if (lane_p == 0) TLD(21, u2x);
            const float st = (((__uint_as_float(s0.x) + __uint_as_float(s0.y)) + (__uint_as_float(s0.z) + __uint_as_float(s0.w))) +
                              ((__uint_as_float(s1.x) + __uint_as_float(s1.y)) + (__uint_as_float(s1.z) + __uint_as_float(s1.w))) + (s2x + s2y)) * (1.0f / 640.0f);
            const float tot = ((__uint_as_float(u0.x) + __uint_as_float(u0.y)) + (__uint_as_float(u0.z) + __uint_as_float(u0.w))) +
                              ((__uint_as_float(u1.x) + __uint_as_float(u1.y)) + (__uint_as_float(u1.z) + __uint_as_float(u1.w))) + (u2x + u2y);
            const float so = __shfl_xor_sync(FULL, st, 1);
            const float cs = __shfl_xor_sync(FULL, tot, 16);
            const float mean = selp(st, so, lane_p & 1), msq = selp(so, st, lane_p & 1);
            const float var = fmaxf(fmaf(-mean, mean, msq), 0.f);
            const float rinv = fast_rcp(bfr(fast_sqrt(bfr(bfr(var) + 1e-5f))));
            const float z = fmaxf(fmaf(-bfr(mean), cs, tot) * rinv, 0.f);
            if (lane_p < 16) asm volatile("st.shared.u16 [%0], %1;" :: "r"(h1_w), "h"((unsigned short)pack_bf(z, 0.f)) : "memory");
            bar_arrive(NB_H1, 352);
        }
        if (f >= NOCT) return;
        mbar_wait(bars + BAR_CLR * 8);
        unsigned ha = ld_w1(hb0);
        bar_sync(NB_DSENT, 352);
        spin_cycles(dly_d);
        {
            uint4 v[7];
#pragma unroll
            for (int j = 0; j < 7; j++) v[j] = ld_w4(d_src + 128 * j);
#pragma unroll 1
            for (int n = 0; n < SPIN_LIMIT; n++) {
                if (!__any_sync(FULL, (ha & tag) == 0)) break;
                ha = ld_w1(hb0);
            }
            float hs = __uint_as_float(ha);
            hs += __shfl_xor_sync(FULL, hs, 8);
            hs += __shfl_xor_sync(FULL, hs, 16);
            const float base = bfr(xcol + bfr(hs));
            float r = 0.f;
#pragma unroll 1
            for (int n = 0; n < SPIN_LIMIT; n++) {
                float t0 = ((__uint_as_float(v[0].x) + __uint_as_float(v[1].x)) + (__uint_as_float(v[2].x) + __uint_as_float(v[3].x))) +
                           ((__uint_as_float(v[4].x) + __uint_as_float(v[5].x)) + __uint_as_float(v[6].x));
                float t1 = ((__uint_as_float(v[0].y) + __uint_as_float(v[1].y)) + (__uint_as_float(v[2].y) + __uint_as_float(v[3].y))) +
                           ((__uint_as_float(v[4].y) + __uint_as_float(v[5].y)) + __uint_as_float(v[6].y));
                float t2 = ((__uint_as_float(v[0].z) + __uint_as_float(v[1].z)) + (__uint_as_float(v[2].z) + __uint_as_float(v[3].z))) +
                           ((__uint_as_float(v[4].z) + __uint_as_float(v[5].z)) + __uint_as_float(v[6].z));
                float t3 = ((__uint_as_float(v[0].w) + __uint_as_float(v[1].w)) + (__uint_as_float(v[2].w) + __uint_as_float(v[3].w))) +
                           ((__uint_as_float(v[4].w) + __uint_as_float(v[5].w)) + __uint_as_float(v[6].w));
                asm volatile("" : "+f"(t0), "+f"(t1), "+f"(t2), "+f"(t3));
                bool miss = false;
#pragma unroll
                for (int j = 0; j < 7; j++)
                    if (bad4(v[j], tag)) { v[j] = ld_w4(d_src + 128 * j); miss = true; }
                const bool again = __any_sync(FULL, miss);
                r = octet_reduce(t0, t1, t2, t3, lane_p);
                if (!again) break;
            }
            if (lane_p < 8) asm volatile("st.global.u16 [%0], %1;" :: "l"(o_dst), "h"((unsigned short)pack_bf(base + bfr(r), 0.f)) : "memory");
            if (lane_p == 0) TL(13);
        }
        if (f == 0 && lane == 0) st_w1(scr + PR_EPOCH * PAIR_W, epoch + 1u);
    }
}

unsigned* g_scr_base = nullptr;
int g_w1_promo = 2;
int g_v_promo = 2;
int g_wo_promo = 2;

}

typedef CUresult (*EncodeTiledFn)(CUtensorMap*, CUtensorMapDataType, cuuint32_t, void*, const cuuint64_t*, const cuuint64_t*,
                                  const cuuint32_t*, const cuuint32_t*, CUtensorMapInterleave, CUtensorMapSwizzle,
                                  CUtensorMapL2promotion, CUtensorMapFloatOOBfill);

extern "C" void kernel_launch(void* const* d_in, const int* in_sizes, int n_in, void* d_out, int out_size) {
    (void)in_sizes; (void)n_in; (void)out_size;
    static EncodeTiledFn encode = nullptr;
    if (!encode) {
        cudaFuncSetAttribute(fk::fused_decode_kernel, cudaFuncAttributeMaxDynamicSharedMemorySize, fk::SMEM_BYTES);
        void* fn = nullptr;
        cudaDriverEntryPointQueryResult qres;
        cudaGetDriverEntryPoint("cuTensorMapEncodeTiled", &fn, cudaEnableDefault, &qres);
        encode = (EncodeTiledFn)fn;
        void* sp = nullptr;
        cudaGetSymbolAddress(&sp, fk::g_scr);
        fk::g_scr_base = (unsigned*)(((uintptr_t)sp + (2u << 20) - 1) & ~(uintptr_t)((2u << 20) - 1));
    }
    CUtensorMap map_v, map_w1, map_wo;
    {
        const cuuint64_t dims[2] = {640, 4096}, strides[1] = {1280};
        const cuuint32_t box[2] = {32, 64}, es[2] = {1, 1};
        encode(&map_wo, CU_TENSOR_MAP_DATA_TYPE_BFLOAT16, 2, d_in[4], dims, strides, box, es, CU_TENSOR_MAP_INTERLEAVE_NONE,
               CU_TENSOR_MAP_SWIZZLE_64B, (CUtensorMapL2promotion)fk::g_wo_promo, CU_TENSOR_MAP_FLOAT_OOB_FILL_NONE);
    }
    {
        const cuuint64_t dims[2] = {128, 32 * 4096}, strides[1] = {256};
        const cuuint32_t box[2] = {32, 64}, es[2] = {1, 1};
        encode(&map_v, CU_TENSOR_MAP_DATA_TYPE_BFLOAT16, 2, d_in[2], dims, strides, box, es, CU_TENSOR_MAP_INTERLEAVE_NONE,
               CU_TENSOR_MAP_SWIZZLE_64B, (CUtensorMapL2promotion)fk::g_v_promo, CU_TENSOR_MAP_FLOAT_OOB_FILL_NONE);
    }
    {
        const cuuint64_t dims[2] = {1728, 640}, strides[1] = {3456};
        const cuuint32_t box[2] = {16, 128}, es[2] = {1, 1};
        encode(&map_w1, CU_TENSOR_MAP_DATA_TYPE_BFLOAT16, 2, d_in[6], dims, strides, box, es, CU_TENSOR_MAP_INTERLEAVE_NONE,
               CU_TENSOR_MAP_SWIZZLE_32B, (CUtensorMapL2promotion)fk::g_w1_promo, CU_TENSOR_MAP_FLOAT_OOB_FILL_NONE);
    }
    fk::fused_decode_kernel<<<fk::NCTA, fk::NTHREADS, fk::SMEM_BYTES>>>(
        (const __nv_bfloat16*)d_in[0], (const __nv_bfloat16*)d_in[3], (const __nv_bfloat16*)d_in[1],
        (const __nv_bfloat16*)d_in[7], (__nv_bfloat16*)d_out, fk::g_scr_base,
        map_v, map_w1, map_wo);
}
```

```cpp
#include <cuda_runtime.h>
#include <cuda.h>
#include <cuda_bf16.h>
#include <stdint.h>
#include <stdlib.h>

namespace fk {

constexpr int NCTA = 128;
constexpr int NFFN = 108;
constexpr int NOCT = 80;
constexpr int NWO = 80;
constexpr int NTHREADS = 384;

constexpr int ROW_PITCH = 1296;
constexpr int SM_K = 0;
constexpr int SM_V = 65536;
constexpr int SM_W1 = 131072;
constexpr int SM_W2 = SM_W1 + 640 * 32;
constexpr int SM_QPART = SM_W2 + 16 * ROW_PITCH;
constexpr int SM_P = SM_QPART + 4096;
constexpr int SM_XN = SM_P + 2048;
constexpr int SM_OPART = SM_XN + 2560;
constexpr int SM_ML = SM_OPART + 1024;
constexpr int SM_QS = SM_ML + 64;
constexpr int SM_HP = SM_QS + 256;
constexpr int SM_DP = SM_HP + 32 * 48;
constexpr int SM_H1 = SM_DP + 34 * 48;
constexpr int SM_OF = SM_H1 + 32;
constexpr int SM_TAG = SM_OF + 16 * 144;
constexpr int SM_BAR = SM_TAG + 32;
constexpr int BAR_K = 0, BAR_V = 16, BAR_WO = 32, BAR_W1 = 40, BAR_W2 = 45, BAR_SIDE = 46, BAR_CLR = 47, BAR_KFREE = 48, BAR_O = 49, BAR_HS = 50, NBAR = 51;
constexpr int SMEM_BYTES = SM_BAR + NBAR * 8;

constexpr int SPIN_LIMIT = 1 << 17;
#define NPRE 4

struct Pace {
    int tK;
    int dKV;
    int dWO;
    int dW1;
    int dW2;
    int stag;
    int gap;
    int dlyD;
    int dlyO;
    int nprobe;
    int tP;
    int mode;
    int sV;
};
#define PACE_DEFAULT {1120, 165, 105, 120, 100, 20, 230, 250, 800, 8, 600, 0, 4}

__device__ __align__(4096) unsigned g_scr[1 << 20];
constexpr int PAIR_W = 2048, REP_W = 1024;
constexpr int PR_D = 0;
constexpr int PR_H = 172;
constexpr int PR_O = 84;
constexpr int PR_S = 88;
constexpr int PR_A = 120;
constexpr int PR_SIDE = 136;
constexpr int PR_PROBE = 137;
constexpr int PR_EPOCH = 169;
constexpr int PR_TL = 170;
__device__ __forceinline__ int near_off(int pair, unsigned side) {
    return pair * PAIR_W + (int)((side ^ __popc((2 * pair) & 0xb3)) & 1u) * REP_W;
}
#define TL(i) do {} while (0)
#define TLD(i, v) do {} while (0)
#define TLV(i, v) do {} while (0)

__device__ __forceinline__ unsigned gtime32() {
    unsigned long long t; asm volatile("mov.u64 %0, %globaltimer;" : "=l"(t) :: "memory"); return (unsigned)t;
}
__device__ __forceinline__ uint32_t smem_u32(const void* p) { return (uint32_t)__cvta_generic_to_shared(p); }
__device__ __forceinline__ void mbar_init(uint32_t bar, uint32_t cnt) {
    asm volatile("mbarrier.init.shared::cta.b64 [%0], %1;" :: "r"(bar), "r"(cnt) : "memory");
}
__device__ __forceinline__ void mbar_expect_tx(uint32_t bar, uint32_t bytes) {
    asm volatile("mbarrier.arrive.expect_tx.shared::cta.b64 _, [%0], %1;" :: "r"(bar), "r"(bytes) : "memory");
}
__device__ __forceinline__ void mbar_arrive(uint32_t bar) {
    asm volatile("mbarrier.arrive.shared::cta.b64 _, [%0];" :: "r"(bar) : "memory");
}
__device__ __forceinline__ void mbar_arrive_p(uint32_t bar, unsigned p) {
    asm volatile("{\n.reg .pred p;\nsetp.ne.u32 p, %1, 0;\n@p mbarrier.arrive.shared::cta.b64 _, [%0];\n}" :: "r"(bar), "r"(p) : "memory");
}
__device__ __forceinline__ bool mbar_test(uint32_t bar) {
    uint32_t ok;
    asm volatile("{\n.reg .pred p;\nmbarrier.test_wait.parity.shared::cta.b64 p, [%1], 0;\nselp.u32 %0, 1, 0, p;\n}"
                 : "=r"(ok) : "r"(bar) : "memory");
    return ok != 0;
}
__device__ __forceinline__ bool mbar_try(uint32_t bar) {
    uint32_t ok;
    asm volatile("{\n.reg .pred p;\nmbarrier.try_wait.parity.shared::cta.b64 p, [%1], 0;\nselp.u32 %0, 1, 0, p;\n}"
                 : "=r"(ok) : "r"(bar) : "memory");
    return ok != 0;
}
__device__ __forceinline__ void mbar_wait(uint32_t bar, int lim = SPIN_LIMIT) {
#pragma unroll 1
    for (int n = 0; n < lim; n++) if (mbar_try(bar)) break;
}
__device__ __forceinline__ uint64_t stream_policy() {
    uint64_t p; asm volatile("createpolicy.fractional.L2::evict_first.b64 %0, 1.0;" : "=l"(p)); return p;
}
__device__ __forceinline__ void bulk_g2s(uint32_t dst, const void* src, uint32_t bytes, uint32_t bar, uint64_t pol) {
    asm volatile("cp.async.bulk.shared::cluster.global.mbarrier::complete_tx::bytes.L2::cache_hint [%0], [%1], %2, [%3], %4;"
                 :: "r"(dst), "l"(src), "r"(bytes), "r"(bar), "l"(pol) : "memory");
}
__device__ __forceinline__ void tma2d(uint32_t dst, const CUtensorMap* map, int c0, int c1, uint32_t bar, uint64_t pol) {
    asm volatile("cp.async.bulk.tensor.2d.shared::cluster.global.mbarrier::complete_tx::bytes.L2::cache_hint [%0], [%1, {%3, %4}], [%2], %5;"
                 :: "r"(dst), "l"(map), "r"(bar), "r"(c0), "r"(c1), "l"(pol) : "memory");
}
__device__ __forceinline__ unsigned tagw(float v, unsigned tag) { return (__float_as_uint(v) & ~3u) | tag; }
__device__ __forceinline__ float untag(unsigned w) { return __uint_as_float(w & ~3u); }
__device__ __forceinline__ void st_w1(unsigned* p, unsigned a) {
    asm volatile("st.relaxed.gpu.global.u32 [%0], %1;" :: "l"(p), "r"(a) : "memory");
}
__device__ __forceinline__ void st_w1_p(unsigned* a, unsigned v, unsigned p) {
    asm volatile("{\n.reg .pred p;\nsetp.ne.u32 p, %2, 0;\n@p st.relaxed.gpu.global.u32 [%0], %1;\n}" :: "l"(a), "r"(v), "r"(p) : "memory");
}
__device__ __forceinline__ void st_w4(unsigned* p, uint4 v) {
    asm volatile("st.relaxed.gpu.global.v4.u32 [%0], {%1,%2,%3,%4};" :: "l"(p), "r"(v.x), "r"(v.y), "r"(v.z), "r"(v.w) : "memory");
}
__device__ __forceinline__ unsigned ld_w1(const unsigned* p) {
    unsigned v;
    asm volatile("ld.relaxed.gpu.global.u32 %0, [%1];" : "=r"(v) : "l"(p) : "memory");
    return v;
}
__device__ __forceinline__ uint4 ld_w4(const unsigned* p) {
    uint4 v;
    asm volatile("ld.relaxed.gpu.global.v4.u32 {%0,%1,%2,%3}, [%4];" : "=r"(v.x), "=r"(v.y), "=r"(v.z), "=r"(v.w) : "l"(p) : "memory");
    return v;
}
__device__ __forceinline__ uint2 ld_w2(const unsigned* p) {
    uint2 v;
    asm volatile("ld.relaxed.gpu.global.v2.u32 {%0,%1}, [%2];" : "=r"(v.x), "=r"(v.y) : "l"(p) : "memory");
    return v;
}
__device__ __forceinline__ bool bad2(uint2 v, unsigned tag) { return (v.x & v.y & tag) == 0; }
__device__ __forceinline__ bool bad4(uint4 v, unsigned tag) { return ((v.x & v.y & v.z) & v.w & tag) == 0; }

__device__ __forceinline__ void bar_sync(int id, int n) { __syncwarp(); asm volatile("bar.sync %0, %1;" :: "r"(id), "r"(n) : "memory"); }
__device__ __forceinline__ void bar_arrive(int id, int n) { __syncwarp(); asm volatile("bar.arrive %0, %1;" :: "r"(id), "r"(n) : "memory"); }
template <int ID, int N> __device__ __forceinline__ void bar_sync_p(unsigned p) {
    __syncwarp();
    asm volatile("{\n.reg .pred p;\nsetp.ne.u32 p, %0, 0;\n@p bar.sync %1, %2;\n}" :: "r"(p), "n"(ID), "n"(N) : "memory");
}
template <int ID, int N> __device__ __forceinline__ void bar_arrive_p(unsigned p) {
    __syncwarp();
    asm volatile("{\n.reg .pred p;\nsetp.ne.u32 p, %0, 0;\n@p bar.arrive %1, %2;\n}" :: "r"(p), "n"(ID), "n"(N) : "memory");
}
__device__ __forceinline__ void sts_p(uint32_t a, float v, unsigned p) {
    asm volatile("{\n.reg .pred p;\nsetp.ne.u32 p, %2, 0;\n@p st.shared.f32 [%0], %1;\n}" :: "r"(a), "f"(v), "r"(p) : "memory");
}
__device__ __forceinline__ float bf_lo(unsigned u) { return __uint_as_float(u << 16); }
__device__ __forceinline__ float bf_hi(unsigned u) { return __uint_as_float(u & 0xffff0000u); }
__device__ __forceinline__ unsigned pack_bf(float lo, float hi) {
    unsigned r; asm("cvt.rn.bf16x2.f32 %0, %1, %2;" : "=r"(r) : "f"(hi), "f"(lo)); return r;
}
__device__ __forceinline__ float bfr(float v) { return __uint_as_float(pack_bf(0.f, v)); }
__device__ __forceinline__ float selp(float a, float b, unsigned c) {
    float r; asm("{\n.reg .pred p;\nsetp.ne.u32 p, %3, 0;\nselp.f32 %0, %1, %2, p;\n}" : "=f"(r) : "f"(a), "f"(b), "r"(c)); return r;
}
__device__ __forceinline__ float sel4(float a0, float a1, float a2, float a3, int t) {
    return selp(selp(a3, a2, t & 1), selp(a1, a0, t & 1), t & 2);
}
__device__ __forceinline__ float fast_sqrt(float v) { float r; asm("sqrt.approx.ftz.f32 %0, %1;" : "=f"(r) : "f"(v)); return r; }
__device__ __forceinline__ float fast_rcp(float v) { float r; asm("rcp.approx.ftz.f32 %0, %1;" : "=f"(r) : "f"(v)); return r; }
template <class T> __device__ __forceinline__ T* pin(T* p) { asm volatile("" : "+l"(p)); return p; }
__device__ __forceinline__ void mma16816(float (&c)[4], unsigned a0, unsigned a1, unsigned a2, unsigned a3,
                                         unsigned b0, unsigned b1) {
    asm volatile("mma.sync.aligned.m16n8k16.row.col.f32.bf16.bf16.f32 {%0,%1,%2,%3}, {%4,%5,%6,%7}, {%8,%9}, {%0,%1,%2,%3};"
                 : "+f"(c[0]), "+f"(c[1]), "+f"(c[2]), "+f"(c[3])
                 : "r"(a0), "r"(a1), "r"(a2), "r"(a3), "r"(b0), "r"(b1));
}
__device__ __forceinline__ uint4 ldsm4t(uint32_t addr) {
    uint4 r;
    asm volatile("ldmatrix.sync.aligned.m8n8.x4.trans.shared.b16 {%0,%1,%2,%3}, [%4];"
                 : "=r"(r.x), "=r"(r.y), "=r"(r.z), "=r"(r.w) : "r"(addr) : "memory");
    return r;
}
__device__ __forceinline__ uint4 lds16(uint32_t addr) {
    uint4 r;
    asm volatile("ld.shared.v4.u32 {%0,%1,%2,%3}, [%4];" : "=r"(r.x), "=r"(r.y), "=r"(r.z), "=r"(r.w) : "r"(addr) : "memory");
    return r;
}
__device__ __forceinline__ void wait_until(unsigned t0, int t) {
#pragma unroll 1
    for (int n = 0; n < SPIN_LIMIT; n++) if ((int)(gtime32() - t0) >= t) break;
}
__device__ __forceinline__ void spin_cycles(int n) {
    if (n > 0) { const unsigned c0 = clock(); while ((int)(clock() - c0) < n) {} }
}
__device__ __forceinline__ float octet_reduce(float v0, float v1, float v2, float v3, int lane) {
    const unsigned FULL = 0xffffffffu;
    const unsigned b1 = lane & 2, b2 = lane & 4;
    float k0 = selp(v2, v0, b1), k1 = selp(v3, v1, b1);
    const float s0 = selp(v0, v2, b1), s1 = selp(v1, v3, b1);
    k0 += __shfl_xor_sync(FULL, s0, 2);
    k1 += __shfl_xor_sync(FULL, s1, 2);
    float k = selp(k1, k0, b2);
    const float s = selp(k0, k1, b2);
    k += __shfl_xor_sync(FULL, s, 4);
    k += __shfl_xor_sync(FULL, k, 8);
    k += __shfl_xor_sync(FULL, k, 16);
    return k;
}

constexpr int NB_XN = 1, NB_QPART = 2, NB_Q = 3, NB_OPART = 4, NB_FPART = 5, NB_DSENT = 6, NB_H1 = 7, NB_PROBE = 8, NB_TAG0 = 9, NB_TAG1 = 10, NB_HP = 11;
constexpr int N_XN = NTHREADS - 64;

__global__ void __launch_bounds__(NTHREADS, 1)
fused_decode_kernel(const __nv_bfloat16* __restrict__ x, const __nv_bfloat16* __restrict__ wq,
                    const __nv_bfloat16* __restrict__ kc,
                    const __nv_bfloat16* __restrict__ w2, __nv_bfloat16* __restrict__ out, unsigned* __restrict__ scr,
                    const __grid_constant__ CUtensorMap map_v, const __grid_constant__ CUtensorMap map_w1,
                    const __grid_constant__ CUtensorMap map_wo) {
    constexpr Pace pc = PACE_DEFAULT;
    extern __shared__ __align__(1024) unsigned char smem[];
    const unsigned tstart = gtime32();
    const int tid = threadIdx.x, warp = tid >> 5, lane = tid & 31;
    const int b = blockIdx.x, h = b >> 2, c = b & 3;
    const int cw = warp - 2, ct = tid - 64;

    uint2 xr[5];
    unsigned epoch;
    uint4 wr[10];
    {
        const char* wp = reinterpret_cast<const char*>(wq) + (size_t)(160 * c + (ct >> 4)) * 8192 + h * 256 + (ct & 15) * 16;
        const uint2* xp = reinterpret_cast<const uint2*>(x) + lane;
        asm volatile("{\n.reg .pred p;\nsetp.ne.u32 p, %13, 0;\n@p bra.uni XSKIP;\n"
                     "ld.global.nc.v2.u32 {%0,%1}, [%11];\nld.global.nc.v2.u32 {%2,%3}, [%11+256];\nld.global.nc.v2.u32 {%4,%5}, [%11+512];\n"
                     "ld.global.nc.v2.u32 {%6,%7}, [%11+768];\nld.global.nc.v2.u32 {%8,%9}, [%11+1024];\n"
                     "ld.relaxed.gpu.global.u32 %10, [%12];\nXSKIP:\n}"
                     : "=r"(xr[0].x), "=r"(xr[0].y), "=r"(xr[1].x), "=r"(xr[1].y), "=r"(xr[2].x), "=r"(xr[2].y), "=r"(xr[3].x), "=r"(xr[3].y),
                       "=r"(xr[4].x), "=r"(xr[4].y), "=r"(epoch)
                     : "l"(xp), "l"(scr + PR_EPOCH * PAIR_W), "r"(warp) : "memory");
        asm volatile("{\n.reg .pred p;\nsetp.ge.u32 p, %41, 8;\n@p bra.uni WSKIP;\n"
                     "ld.global.nc.L1::no_allocate.v4.u32 {%0,%1,%2,%3}, [%40];\n"
                     "ld.global.nc.L1::no_allocate.v4.u32 {%4,%5,%6,%7}, [%40+131072];\n"
                     "ld.global.nc.L1::no_allocate.v4.u32 {%8,%9,%10,%11}, [%40+262144];\n"
                     "ld.global.nc.L1::no_allocate.v4.u32 {%12,%13,%14,%15}, [%40+393216];\n"
                     "ld.global.nc.L1::no_allocate.v4.u32 {%16,%17,%18,%19}, [%40+524288];\n"
                     "ld.global.nc.L1::no_allocate.v4.u32 {%20,%21,%22,%23}, [%40+655360];\n"
                     "ld.global.nc.L1::no_allocate.v4.u32 {%24,%25,%26,%27}, [%40+786432];\n"
                     "ld.global.nc.L1::no_allocate.v4.u32 {%28,%29,%30,%31}, [%40+917504];\n"
                     "ld.global.nc.L1::no_allocate.v4.u32 {%32,%33,%34,%35}, [%40+1048576];\n"
                     "ld.global.nc.L1::no_allocate.v4.u32 {%36,%37,%38,%39}, [%40+1179648];\n"
                     "WSKIP:\n}"
                     : "=r"(wr[0].x), "=r"(wr[0].y), "=r"(wr[0].z), "=r"(wr[0].w), "=r"(wr[1].x), "=r"(wr[1].y), "=r"(wr[1].z), "=r"(wr[1].w),
                       "=r"(wr[2].x), "=r"(wr[2].y), "=r"(wr[2].z), "=r"(wr[2].w), "=r"(wr[3].x), "=r"(wr[3].y), "=r"(wr[3].z), "=r"(wr[3].w),
                       "=r"(wr[4].x), "=r"(wr[4].y), "=r"(wr[4].z), "=r"(wr[4].w), "=r"(wr[5].x), "=r"(wr[5].y), "=r"(wr[5].z), "=r"(wr[5].w),
                       "=r"(wr[6].x), "=r"(wr[6].y), "=r"(wr[6].z), "=r"(wr[6].w), "=r"(wr[7].x), "=r"(wr[7].y), "=r"(wr[7].z), "=r"(wr[7].w),
                       "=r"(wr[8].x), "=r"(wr[8].y), "=r"(wr[8].z), "=r"(wr[8].w), "=r"(wr[9].x), "=r"(wr[9].y), "=r"(wr[9].z), "=r"(wr[9].w)
                     : "l"(wp), "r"(cw));
    }
    if (ct == 0) TL(15);

    const uint32_t sb = smem_u32(smem);
    const uint32_t bars = sb + SM_BAR;
    const int g = lane >> 2, t = lane & 3;
    const unsigned FULL = 0xffffffffu;
    volatile unsigned* const misc = reinterpret_cast<volatile unsigned*>(smem + SM_TAG);
    const int f = (b >= NWO) ? b - NWO : b + (NCTA - NWO);

    if ((unsigned)cw < 10u) {
        const int mi = lane >> 3, ri = lane & 7;
        unsigned tag, side, sd0, sd1;
        const int oct = 2 * (4 * cw + t);
        const unsigned xpair = __ldg(reinterpret_cast<const unsigned*>(x) + ct);
        if (cw < 8) {
            bar_sync(NB_XN, N_XN);
            tag = misc[0];
            unsigned* const s_dst = scr + (PR_S + h) * PAIR_W + c * 256 + (cw + 8 * (t >> 1)) * 16 + 8 * (t & 1) + g;
            st_w1(s_dst, 0u); st_w1(s_dst + REP_W, 0u);
            {
                const float* xn = reinterpret_cast<const float*>(smem + SM_XN) + 160 * c + (ct >> 4);
                float acc[8];
#pragma unroll
                for (int j = 0; j < 8; j++) acc[j] = 0.f;
#pragma unroll
                for (int i = 0; i < 10; i++) {
                    const float xv = xn[16 * i];
                    acc[0] = fmaf(xv, bf_lo(wr[i].x), acc[0]); acc[1] = fmaf(xv, bf_hi(wr[i].x), acc[1]);
                    acc[2] = fmaf(xv, bf_lo(wr[i].y), acc[2]); acc[3] = fmaf(xv, bf_hi(wr[i].y), acc[3]);
                    acc[4] = fmaf(xv, bf_lo(wr[i].z), acc[4]); acc[5] = fmaf(xv, bf_hi(wr[i].z), acc[5]);
                    acc[6] = fmaf(xv, bf_lo(wr[i].w), acc[6]); acc[7] = fmaf(xv, bf_hi(wr[i].w), acc[7]);
                }
#pragma unroll
                for (int j = 0; j < 8; j++) acc[j] += __shfl_xor_sync(FULL, acc[j], 16);
                if (lane < 16) {
                    float4* qp = reinterpret_cast<float4*>(smem + SM_QPART + cw * 512 + lane * 32);
                    qp[0] = make_float4(acc[0], acc[1], acc[2], acc[3]);
                    qp[1] = make_float4(acc[4], acc[5], acc[6], acc[7]);
                }
            }
            bar_arrive(NB_QPART, 288);
            if (pc.mode == 1) return;
            bar_sync(NB_Q, 288);
            uint4 qf[4];
#pragma unroll
            for (int j = 0; j < 4; j++) qf[j] = lds16(sb + SM_QS + 16 * (t + 4 * (j ^ (g & 1))));
            float mys = 0.f;
#pragma unroll 1
            for (int tile = 0; tile < 2; tile++) {
                const int ch = cw + 8 * tile;
                mbar_wait(bars + (BAR_K + ch) * 8);
                const uint32_t kb = sb + SM_K + ch * 4096 + g * 256 + t * 16;
                float cA[4] = {0.f, 0.f, 0.f, 0.f}, cB[4] = {0.f, 0.f, 0.f, 0.f};
#pragma unroll
                for (int j = 0; j < 4; j++) {
                    const uint32_t a = kb + 64 * (j ^ (g & 1));
                    const uint4 ra = lds16(a), rb = lds16(a + 2048);
                    mma16816(cA, ra.x, rb.x, ra.y, rb.y, qf[j].x, qf[j].y);
                    mma16816(cB, ra.z, rb.z, ra.w, rb.w, qf[j].z, qf[j].w);
                }
                const float s0 = selp(cA[1] + cB[1], cA[0] + cB[0], g & 1);
                const float s1 = selp(cA[3] + cB[3], cA[2] + cB[2], g & 1);
                mys = selp(selp(s1, s0, t & 1), mys, (t >> 1) == tile);
            }
            __syncwarp();
            if (lane == 0) mbar_arrive(bars + BAR_KFREE * 8);
            mys = bfr(bfr(mys) * 0.08838834764831845f);
            st_w1(s_dst, __float_as_uint(mys) | tag);
            st_w1(s_dst + REP_W, __float_as_uint(mys) | tag);
            if (ct == 224) TL(3);
            {
                mbar_wait(bars + (BAR_V + pc.sV) * 8);
                mbar_wait(bars + BAR_SIDE * 8);
                const unsigned* ps = scr + near_off(PR_S + h, misc[1]) + (cw + 8 * (lane >> 4)) * 64 + 4 * (lane & 15);
                uint4 v = ld_w4(ps);
#pragma unroll 1
                for (int n = 0; n < SPIN_LIMIT; n++) {
                    if (!__any_sync(FULL, bad4(v, tag))) break;
                    __nanosleep(50);
                    v = ld_w4(ps);
                }
                if (ct == 224) TL(28);
                const float e0 = untag(v.x), e1 = untag(v.y), e2 = untag(v.z), e3 = untag(v.w);
                float m = fmaxf(fmaxf(e0, e1), fmaxf(e2, e3));
#pragma unroll
                for (int o = 16; o; o >>= 1) m = fmaxf(m, __shfl_xor_sync(FULL, m, o));
                const unsigned p01 = pack_bf(__expf(e0 - m), __expf(e1 - m)), p23 = pack_bf(__expf(e2 - m), __expf(e3 - m));
                reinterpret_cast<uint2*>(smem + SM_P)[cw * 32 + lane] = make_uint2(p01, p23);
                float l = (bf_lo(p01) + bf_hi(p01)) + (bf_lo(p23) + bf_hi(p23));
#pragma unroll
                for (int o = 16; o; o >>= 1) l += __shfl_xor_sync(FULL, l, o);
                if (lane == 0) reinterpret_cast<float2*>(smem + SM_ML)[cw] = make_float2(m, l);
                __syncwarp();
                if (ct == 224) TL(5);
            }
            float o0[4] = {0.f, 0.f, 0.f, 0.f}, o1[4] = {0.f, 0.f, 0.f, 0.f};
            const int vrow = (mi >> 1) * 8 + ri;
            const uint32_t va0 = vrow * 64 + (((mi & 1) ^ ((ri >> 1) & 3)) * 16);
            const uint32_t va1 = vrow * 64 + (((2 + (mi & 1)) ^ ((ri >> 1) & 3)) * 16);
#pragma unroll 1
            for (int tile = 0; tile < 2; tile++) {
                const int ch = cw + 8 * tile;
                const unsigned* pp = reinterpret_cast<const unsigned*>(smem + SM_P) + cw * 64 + tile * 32 + t;
                unsigned pf[8];
#pragma unroll
                for (int s = 0; s < 8; s++) pf[s] = pp[4 * s];
                mbar_wait(bars + (BAR_V + ch) * 8);
                const uint32_t vb = sb + SM_V + ch * 4096;
#pragma unroll
                for (int s = 0; s < 4; s++) {
                    const uint4 a0 = ldsm4t(vb + s * 1024 + va0), a1 = ldsm4t(vb + s * 1024 + va1);
                    mma16816(o0, a0.x, a0.y, a0.z, a0.w, pf[2 * s], pf[2 * s + 1]);
                    mma16816(o1, a1.x, a1.y, a1.z, a1.w, pf[2 * s], pf[2 * s + 1]);
                }
            }
            reinterpret_cast<float*>(smem + SM_OPART)[cw * 32 + 8 * t + g] = sel4(o0[0], o0[2], o1[0], o1[2], t);
            bar_arrive(NB_OPART, 288);
            side = misc[1];
            sd0 = ld_w1(scr + near_off(PR_SIDE, side) + oct * 8); sd1 = ld_w1(scr + near_off(PR_SIDE, side) + oct * 8 + 8);
            if (b < NWO) {
                const int ks = cw >> 1;
                const uint32_t ab = sb + SM_K + (cw & 1) * 4096 + (16 * ks + (mi >> 1) * 8 + ri) * 64;
                const uint32_t ab0 = ab + (((mi & 1) ^ ((ri >> 1) & 3)) * 16), ab1 = ab + (((2 + (mi & 1)) ^ ((ri >> 1) & 3)) * 16);
                uint4 a[2 * NPRE];
#pragma unroll
                for (int i = 0; i < NPRE; i++) {
                    mbar_wait(bars + (BAR_WO + i) * 8);
                    a[2 * i] = ldsm4t(ab0 + i * 8192); a[2 * i + 1] = ldsm4t(ab1 + i * 8192);
                }
                mbar_wait(bars + BAR_O * 8);
                uint4 bf[4];
#pragma unroll
                for (int i = 0; i < 4; i++) bf[i] = lds16(sb + SM_OF + (ks * 4 + t) * 144 + (cw & 1) * 64 + i * 16);
                float cc[4][4];
#pragma unroll
                for (int i = 0; i < 4; i++) cc[i][0] = cc[i][1] = cc[i][2] = cc[i][3] = 0.f;
#pragma unroll
                for (int i = 0; i < 8; i++) {
                    uint4 a0, a1;
                    if (i < NPRE) { a0 = a[2 * i]; a1 = a[2 * i + 1]; }
                    else {
                        mbar_wait(bars + (BAR_WO + i) * 8);
                        a0 = ldsm4t(ab0 + i * 8192); a1 = ldsm4t(ab1 + i * 8192);
                    }
                    const unsigned b0 = (i & 1) ? bf[i >> 1].z : bf[i >> 1].x, b1 = (i & 1) ? bf[i >> 1].w : bf[i >> 1].y;
                    mma16816(cc[2 * (i & 1)], a0.x, a0.y, a0.z, a0.w, b0, b1);
                    mma16816(cc[2 * (i & 1) + 1], a1.x, a1.y, a1.z, a1.w, b0, b1);
                }
                sts_p(sb + SM_HP + ((8 * t + g) * 12 + cw) * 4,
                      sel4(cc[0][0] + cc[2][0], cc[0][2] + cc[2][2], cc[1][0] + cc[3][0], cc[1][2] + cc[3][2], t), 1u);
                bar_arrive(NB_HP, 288);
                if (ct == 0) TL(6);
            }
        } else {
            unsigned* const probe = scr + near_off(PR_PROBE + (b >> 2), cw & 1) + (b & 3) * 256;
            st_w1(probe + (lane >> 3) * 32 + (lane & 7), 0u);
            st_w1(probe + 128 + (lane >> 3) * 32 + (lane & 7), 0u);
            if (cw == 8 && lane == 0) misc[2] = 0u;
            wait_until(tstart, pc.tP);
            bar_sync(NB_PROBE, 64);
            unsigned v = 0;
#pragma unroll 1
            for (int i = 0; i < pc.nprobe; i++) v = ld_w1(probe + i * 32 + v);
            unsigned won = 0;
            if (lane == 0) won = (atomicExch(reinterpret_cast<unsigned*>(smem + SM_TAG) + 2, 1u + v) == 0u);
            won = __shfl_sync(FULL, won, 0);
            if (cw & 1) bar_sync(NB_TAG1, 64); else bar_sync(NB_TAG0, 64);
            tag = misc[0];
            if (pc.mode == 1) return;
            if (won) {
                const unsigned sd = cw & 1;
                if (lane == 0) {
                    misc[1] = sd;
                    mbar_arrive(bars + BAR_SIDE * 8);
                    TL(23);
                }
                if (f < NOCT) {
                    unsigned* i1 = scr + near_off(PR_D + f, sd) + 4 * lane;
#pragma unroll
                    for (int j = 0; j < 7; j++) {
                        const unsigned z = (j * 16 + (lane >> 1) >= NFFN) ? tag : 0u;
                        st_w4(i1 + 128 * j, make_uint4(z, z, z, z));
                    }
                    asm volatile("fence.acq_rel.gpu;" ::: "memory");
                    __syncwarp();
                    if (lane < 16) st_w1(scr + PR_SIDE * PAIR_W + (lane >> 3) * REP_W + f * 8 + (lane & 7), (sd << 2) | tag);
                    if (lane == 0) { mbar_arrive(bars + BAR_CLR * 8); TL(30); }
                }
            }
            mbar_wait(bars + (BAR_V + 15) * 8);
            mbar_wait(bars + BAR_SIDE * 8);
            side = misc[1];
            sd0 = ld_w1(scr + near_off(PR_SIDE, side) + oct * 8); sd1 = ld_w1(scr + near_off(PR_SIDE, side) + oct * 8 + 8);
            if (b < NWO) {
                const unsigned* po = scr + near_off(PR_O + b / 20, side) + (cw & 1) * 512 + 4 * lane;
                unsigned* of = reinterpret_cast<unsigned*>(smem + SM_OF) + (((lane >> 2) & 3) * 4 + 2 * (lane & 1)) * 36 +
                               (lane >> 4) * 16 + 8 * (cw & 1) + ((lane >> 1) & 1);
                spin_cycles(pc.dlyO);
                uint4 ov[4];
#pragma unroll
                for (int q = 0; q < 4; q++) ov[q] = ld_w4(po + 128 * q);
#pragma unroll 1
                for (int n = 0; n < SPIN_LIMIT; n++) {
                    bool miss = false;
#pragma unroll
                    for (int q = 0; q < 4; q++) if (bad4(ov[q], tag)) { ov[q] = ld_w4(po + 128 * q); miss = true; }
                    if (!__any_sync(FULL, miss)) break;
                }
#pragma unroll
                for (int q = 0; q < 4; q++) {
                    of[2 * q] = __byte_perm(ov[q].x, ov[q].y, 0x7632);
                    of[2 * q + 36] = __byte_perm(ov[q].z, ov[q].w, 0x7632);
                }
                __syncwarp();
                if (lane == 0) { mbar_arrive(bars + BAR_O * 8); if (cw == 8) TL(29); }
            }
        }
        if (f >= NFFN) return;

        const unsigned* const sd_src = scr + near_off(PR_SIDE, side) + oct * 8;
        const unsigned* const h_src0 = pin(scr + near_off(PR_H + 4 * (b & 1), side) + 2 * ct);
        const unsigned* const h_src1 = pin(scr + near_off(PR_H + 4 * (b & 1) + 1, side) + 2 * ct);
        const unsigned* const h_src2 = pin(scr + near_off(PR_H + 4 * (b & 1) + 2, side) + 2 * ct);
        const unsigned* const h_src3 = pin(scr + near_off(PR_H + 4 * (b & 1) + 3, side) + 2 * ct);
#pragma unroll 1
        for (int n = 0; n < SPIN_LIMIT; n++) {
            if (!__any_sync(FULL, (sd0 & sd1 & tag) == 0)) break;
            __nanosleep(100);
            sd0 = ld_w1(sd_src); sd1 = ld_w1(sd_src + 8);
        }
        unsigned* const d_a = pin(scr + near_off(PR_D + oct, sd0 >> 2) + f * 8 + g);
        unsigned* const d_b = pin(scr + near_off(PR_D + oct + 1, sd1 >> 2) + f * 8 + g);
        uint32_t dp_w = sb + SM_DP + ((g + 8 * t) * 12 + cw) * 4;
        uint32_t st_w = sb + SM_DP + ((32 + lane) * 12 + cw) * 4;
        uint32_t w2_r = sb + SM_W2 + ((mi >> 1) * 8 + ri) * ROW_PITCH + cw * 128 + (mi & 1) * 16;
        uint32_t w1_r = sb + SM_W1 + (64 * cw + (mi >> 1) * 8 + ri) * 32 + (((mi & 1) ^ (ri >> 2)) * 16);
        uint32_t w1_bar = bars + (BAR_W1 + (cw >> 1)) * 8;
        asm volatile("" : "+r"(dp_w), "+r"(st_w), "+r"(w2_r), "+r"(w1_r), "+r"(w1_bar));
        mbar_wait(bars + ((b < NWO) ? BAR_HS : BAR_W1) * 8);
        uint2 h0 = ld_w2(h_src0), h1 = ld_w2(h_src1), h2 = ld_w2(h_src2), h3 = ld_w2(h_src3);
        uint4 a[4];
        bool w1_in = false;
#pragma unroll 1
        for (int n = 0; n < SPIN_LIMIT; n++) {
            if (!w1_in && mbar_test(w1_bar)) {
                w1_in = true;
#pragma unroll
                for (int s = 0; s < 4; s++) a[s] = ldsm4t(w1_r + s * 512);
            }
            bool miss = false;
            if (bad2(h0, tag)) { h0 = ld_w2(h_src0); miss = true; }
            if (bad2(h1, tag)) { h1 = ld_w2(h_src1); miss = true; }
            if (bad2(h2, tag)) { h2 = ld_w2(h_src2); miss = true; }
            if (bad2(h3, tag)) { h3 = ld_w2(h_src3); miss = true; }
            if (!__any_sync(FULL, miss)) break;
        }
        const unsigned att = pack_bf((__uint_as_float(h0.x) + __uint_as_float(h1.x)) + (__uint_as_float(h2.x) + __uint_as_float(h3.x)),
                                     (__uint_as_float(h0.y) + __uint_as_float(h1.y)) + (__uint_as_float(h2.y) + __uint_as_float(h3.y)));
        const unsigned hpair = pack_bf(bf_lo(xpair) + bf_lo(att), bf_hi(xpair) + bf_hi(att));
        if (ct == 0) TL(8);
        unsigned hf[8];
#pragma unroll
        for (int s = 0; s < 8; s++) hf[s] = __shfl_sync(FULL, hpair, 4 * s + t);
        {
            float sA[4] = {0.f, 0.f, 0.f, 0.f}, sB[4] = {0.f, 0.f, 0.f, 0.f};
#pragma unroll
            for (int s = 0; s < 4; s += 2) {
                mma16816(sA, hf[2 * s], 0x3F803F80u, hf[2 * s + 1], 0x3F803F80u, hf[2 * s], hf[2 * s + 1]);
                mma16816(sB, hf[2 * s + 2], 0x3F803F80u, hf[2 * s + 3], 0x3F803F80u, hf[2 * s + 2], hf[2 * s + 3]);
            }
            if (!w1_in) {
                mbar_wait(w1_bar);
#pragma unroll
                for (int s = 0; s < 4; s++) a[s] = ldsm4t(w1_r + s * 512);
            }
            float dA[4] = {0.f, 0.f, 0.f, 0.f}, dB[4] = {0.f, 0.f, 0.f, 0.f};
#pragma unroll
            for (int s = 0; s < 8; s++) hf[s] = (g < 4) ? hf[s] : 0x3F803F80u;
#pragma unroll
            for (int s = 0; s < 4; s += 2) {
                mma16816(dA, a[s].x, a[s].y, a[s].z, a[s].w, hf[2 * s], hf[2 * s + 1]);
                mma16816(dB, a[s + 1].x, a[s + 1].y, a[s + 1].z, a[s + 1].w, hf[2 * s + 2], hf[2 * s + 3]);
            }
            sts_p(st_w, selp(sA[2] + sB[2], sA[0] + sB[0], lane), lane < 2);
            sts_p(dp_w, selp(dA[2] + dB[2], dA[0] + dB[0], t & 1), 1u);
        }
        if (ct == 0) TL(7);
        bar_arrive(NB_FPART, 352);
        uint4 w[4];
        mbar_wait(bars + BAR_W2 * 8);
#pragma unroll
        for (int j = 0; j < 4; j++) w[j] = ldsm4t(w2_r + j * 32);
        bar_sync(NB_H1, 352);
        unsigned b0, b1;
        asm volatile("ld.shared.u32 %0, [%1];" : "=r"(b0) : "r"(sb + SM_H1 + 4 * t) : "memory");
        asm volatile("ld.shared.u32 %0, [%1];" : "=r"(b1) : "r"(sb + SM_H1 + 16 + 4 * t) : "memory");
        float y[4][4];
#pragma unroll
        for (int j = 0; j < 4; j++) {
            y[j][0] = y[j][1] = y[j][2] = y[j][3] = 0.f;
            mma16816(y[j], w[j].x, w[j].y, w[j].z, w[j].w, b0, b1);
        }
        st_w1(d_a, tagw(sel4(y[0][0], y[1][0], y[2][0], y[3][0], t), tag));
        st_w1(d_b, tagw(sel4(y[0][2], y[1][2], y[2][2], y[3][2], t), tag));
        if (ct == 0) TL(9);
        if (f < NOCT) bar_arrive(NB_DSENT, 352);
    } else if (warp == 1) {
        const unsigned t0 = tstart + (unsigned)((h & 7) * pc.stag);
        if (lane == 0) {
            TLV(0, tstart);
#pragma unroll
            for (int i = 0; i < BAR_KFREE; i++) mbar_init(bars + i * 8, 1);
            mbar_init(bars + BAR_KFREE * 8, 8);
            mbar_init(bars + BAR_O * 8, 2);
            mbar_init(bars + BAR_HS * 8, 1);
            asm volatile("fence.mbarrier_init.release.cluster;" ::: "memory");
            asm volatile("prefetch.tensormap [%0];" :: "l"(&map_v) : "memory");
            asm volatile("prefetch.tensormap [%0];" :: "l"(&map_w1) : "memory");
            asm volatile("prefetch.tensormap [%0];" :: "l"(&map_wo) : "memory");
        }
        bar_arrive(NB_XN, N_XN);
        if (lane == 0) {
            int tt = pc.tK;
            const uint64_t pol = stream_policy();
            const char* ks = reinterpret_cast<const char*>(kc) + (size_t)h * 1048576 + 786432 + c * 65536;
#pragma unroll 1
            for (int ii = 0; ii < 16; ii++) {
                const int i = ii;
                wait_until(t0, tt); tt += pc.dKV;
                mbar_expect_tx(bars + (BAR_K + i) * 8, 4096);
                bulk_g2s(sb + SM_K + i * 4096, ks + i * 4096, 4096, bars + (BAR_K + i) * 8, pol);
            }
#pragma unroll 1
            for (int ii = 0; ii < 16; ii++) {
                const int i = ii;
                wait_until(t0, tt); tt += pc.dKV;
                mbar_expect_tx(bars + (BAR_V + i) * 8, 4096);
                tma2d(sb + SM_V + i * 4096, &map_v, 32 * c, h * 4096 + 3072 + 64 * i, bars + (BAR_V + i) * 8, pol);
            }
            if (b < NWO) {
                const int c0 = 32 * (b % 20), r0 = 1024 * (b / 20);
                if (pc.mode != 1) mbar_wait(bars + BAR_KFREE * 8);
#pragma unroll 1
                for (int i = 0; i < 16; i++) {
                    wait_until(t0, tt + i * pc.dWO);
                    if (!(i & 1)) mbar_expect_tx(bars + (BAR_WO + (i >> 1)) * 8, 8192);
                    tma2d(sb + SM_K + i * 4096, &map_wo, c0, r0 + 64 * i, bars + (BAR_WO + (i >> 1)) * 8, pol);
                }
            }
            tt += 16 * pc.dWO + pc.gap;
            if (f < NFFN) {
#pragma unroll 1
                for (int j = 0; j < 5; j++) {
                    wait_until(t0, tt); tt += pc.dW1;
                    mbar_expect_tx(bars + (BAR_W1 + j) * 8, 4096);
                    tma2d(sb + SM_W1 + j * 4096, &map_w1, 16 * f, 128 * j, bars + (BAR_W1 + j) * 8, pol);
                }
                const char* w2s = reinterpret_cast<const char*>(w2) + (size_t)f * 16 * 1280;
                mbar_expect_tx(bars + BAR_W2 * 8, 16 * 1280);
#pragma unroll 1
                for (int j = 0; j < 4; j++) {
                    wait_until(t0, tt); tt += pc.dW2;
#pragma unroll
                    for (int i = 0; i < 4; i++) {
                        const int r = j * 4 + i;
                        bulk_g2s(sb + SM_W2 + r * ROW_PITCH, w2s + r * 1280, 1280, bars + BAR_W2 * 8, pol);
                    }
                }
                TL(10);
            }
            if (pc.mode == 1) {
                for (int i = 0; i < BAR_SIDE; i++)
                    if (i < BAR_WO || (i < BAR_W1 ? b < NWO : f < NFFN)) mbar_wait(bars + i * 8);
            }
        }
    } else {
        const int col = 8 * f + 4 * (lane & 1) + (lane & 2) + ((lane >> 2) & 1);
        float xcol = 0.f;
        if (f < NOCT) xcol = __bfloat162float(x[col]);
        {
            float s = 0.f;
#pragma unroll
            for (int j = 0; j < 5; j++) s += (bf_lo(xr[j].x) + bf_hi(xr[j].x)) + (bf_lo(xr[j].y) + bf_hi(xr[j].y));
#pragma unroll
            for (int o = 16; o; o >>= 1) s += __shfl_xor_sync(FULL, s, o);
            const float mean = s * (1.0f / 640.0f);
            float v = 0.f;
#pragma unroll
            for (int j = 0; j < 5; j++) {
                float d0 = bf_lo(xr[j].x) - mean, d1 = bf_hi(xr[j].x) - mean, d2 = bf_lo(xr[j].y) - mean, d3 = bf_hi(xr[j].y) - mean;
                v += (d0 * d0 + d1 * d1) + (d2 * d2 + d3 * d3);
            }
#pragma unroll
            for (int o = 16; o; o >>= 1) v += __shfl_xor_sync(FULL, v, o);
            const float mb = bfr(mean);
            const float rb = __frcp_rn(bfr(__fsqrt_rn(bfr(bfr(v * (1.0f / 640.0f)) + 1e-5f))));
            float4* xn = reinterpret_cast<float4*>(smem + SM_XN);
#pragma unroll
            for (int j = 0; j < 5; j++) {
                float4 o;
                o.x = bfr(bfr(bf_lo(xr[j].x) - mb) * rb); o.y = bfr(bfr(bf_hi(xr[j].x) - mb) * rb);
                o.z = bfr(bfr(bf_lo(xr[j].y) - mb) * rb); o.w = bfr(bfr(bf_hi(xr[j].y) - mb) * rb);
                xn[j * 32 + lane] = o;
            }
        }
        const unsigned tag = 1u + (epoch & 1u);
        if (lane == 0) misc[0] = tag;
        if (lane == 0) TL(22);
        bar_sync(NB_XN, N_XN);
        bar_arrive(NB_TAG0, 64);
        bar_arrive(NB_TAG1, 64);
        unsigned* const a_dst = scr + (PR_A + (h >> 1)) * PAIR_W + (b & 7) * 128 + 4 * lane;
        unsigned* const h_dst = pin(scr + (PR_H + b / 20) * PAIR_W + 32 * (b % 20) + lane);
        unsigned* const o_msg = pin(scr + (PR_O + (b >> 5)) * PAIR_W + (b & 31) * 32 + lane);
        st_w1(o_msg, 0u); st_w1(o_msg + REP_W, 0u);
        st_w4(a_dst, make_uint4(0u, 0u, 0u, 0u));
        st_w4(a_dst + REP_W, make_uint4(0u, 0u, 0u, 0u));
        if (b < NWO) { st_w1(h_dst, 0u); st_w1(h_dst + REP_W, 0u); st_w1(h_dst + 4 * PAIR_W, 0u); st_w1(h_dst + 4 * PAIR_W + REP_W, 0u); }
        bar_sync(NB_QPART, 288);
        {
            const float4* qp = reinterpret_cast<const float4*>(smem + SM_QPART) + lane;
            float4 s = qp[0];
            if (lane == 0) TLD(1, s.x);
#pragma unroll
            for (int w = 1; w < 8; w++) { const float4 u = qp[w * 32]; s.x += u.x; s.y += u.y; s.z += u.z; s.w += u.w; }
            const uint4 mine = make_uint4(tagw(s.x, tag), tagw(s.y, tag), tagw(s.z, tag), tagw(s.w, tag));
            st_w4(a_dst, mine);
            st_w4(a_dst + REP_W, mine);
            if (pc.mode == 1) return;
            mbar_wait(bars + BAR_SIDE * 8);
            const unsigned* pa = scr + near_off(PR_A + (h >> 1), misc[1]) + (h & 1) * 512 + 4 * lane;
            uint4 v[4];
#pragma unroll 1
            for (int n = 0; n < SPIN_LIMIT; n++) {
#pragma unroll
                for (int cc = 0; cc < 4; cc++) v[cc] = (cc == c) ? mine : ld_w4(pa + cc * 128);
                if (!__any_sync(FULL, bad4(v[0], tag) | bad4(v[1], tag) | bad4(v[2], tag) | bad4(v[3], tag))) break;
                __nanosleep(50);
            }
            const float q0 = ((untag(v[0].x) + untag(v[1].x)) + untag(v[2].x)) + untag(v[3].x);
            const float q1 = ((untag(v[0].y) + untag(v[1].y)) + untag(v[2].y)) + untag(v[3].y);
            const float q2 = ((untag(v[0].z) + untag(v[1].z)) + untag(v[2].z)) + untag(v[3].z);
            const float q3 = ((untag(v[0].w) + untag(v[1].w)) + untag(v[2].w)) + untag(v[3].w);
            reinterpret_cast<uint2*>(smem + SM_QS)[lane] = make_uint2(pack_bf(q0, q1), pack_bf(q2, q3));
        }
        bar_arrive(NB_Q, 288);
        if (lane == 0) TL(2);
        bar_sync(NB_OPART, 288);
        {
            const float* op = reinterpret_cast<const float*>(smem + SM_OPART) + lane;
            const float4* ml = reinterpret_cast<const float4*>(smem + SM_ML);
            const float4 e0 = ml[0], e1 = ml[1], e2 = ml[2], e3 = ml[3];
            const float M = fmaxf(fmaxf(fmaxf(e0.x, e0.z), fmaxf(e1.x, e1.z)), fmaxf(fmaxf(e2.x, e2.z), fmaxf(e3.x, e3.z)));
            const float f0 = __expf(e0.x - M), f1 = __expf(e0.z - M), f2 = __expf(e1.x - M), f3 = __expf(e1.z - M);
            const float f4 = __expf(e2.x - M), f5 = __expf(e2.z - M), f6 = __expf(e3.x - M), f7 = __expf(e3.z - M);
            const float l = ((f0 * e0.y + f1 * e0.w) + (f2 * e1.y + f3 * e1.w)) + ((f4 * e2.y + f5 * e2.w) + (f6 * e3.y + f7 * e3.w));
            float o = ((f0 * op[0] + f1 * op[32]) + (f2 * op[64] + f3 * op[96])) + ((f4 * op[128] + f5 * op[160]) + (f6 * op[192] + f7 * op[224]));
            const unsigned ow = __float_as_uint(bfr(o * fast_rcp(l))) | tag;
            st_w1(o_msg, ow); st_w1(o_msg + REP_W, ow);
            if (lane == 0) TL(4);
        }
        const unsigned side = misc[1];
        const unsigned* const d_src = pin(scr + near_off(PR_D + f, side) + 4 * lane);
        const unsigned* const hb0 = pin(scr + near_off(PR_H + 4 * (b & 1) + (lane >> 3), side) + col);
        __nv_bfloat16* const o_dst = pin(out + col);
        int lane_p = lane, dly_d = pc.dlyD;
        uint32_t hp_r = sb + SM_HP + lane * 48;
        asm volatile("" : "+r"(lane_p), "+r"(dly_d), "+r"(hp_r));
        if (b < NWO) {
            bar_sync(NB_HP, 288);
            const uint4 u0 = lds16(hp_r), u1 = lds16(hp_r + 16);
            const unsigned hw = tagw(((__uint_as_float(u0.x) + __uint_as_float(u0.y)) + (__uint_as_float(u0.z) + __uint_as_float(u0.w))) +
                                     ((__uint_as_float(u1.x) + __uint_as_float(u1.y)) + (__uint_as_float(u1.z) + __uint_as_float(u1.w))), tag);
            st_w1(h_dst, hw); st_w1(h_dst + REP_W, hw); st_w1(h_dst + 4 * PAIR_W, hw); st_w1(h_dst + 4 * PAIR_W + REP_W, hw);
            __syncwarp();
            if (lane_p == 0) mbar_arrive(bars + BAR_HS * 8);
            if (lane_p == 0) TL(12);
        }
        if (f >= NFFN) return;
        {
            uint32_t dp_r = sb + SM_DP + lane * 48, st_r = sb + SM_DP + (32 + (lane & 1)) * 48, h1_w = sb + SM_H1 + 2 * lane;
            asm volatile("" : "+r"(dp_r), "+r"(st_r), "+r"(h1_w));
            bar_sync(NB_FPART, 352);
            const uint4 s0 = lds16(st_r), s1 = lds16(st_r + 16), u0 = lds16(dp_r), u1 = lds16(dp_r + 16);
            float s2x, s2y, u2x, u2y;
            asm volatile("ld.shared.v2.f32 {%0,%1}, [%2];" : "=f"(s2x), "=f"(s2y) : "r"(st_r + 32) : "memory");
            asm volatile("ld.shared.v2.f32 {%0,%1}, [%2];" : "=f"(u2x), "=f"(u2y) : "r"(dp_r + 32) : "memory");
            if (lane_p == 0) TLD(21, u2x);
            const float st = (((__uint_as_float(s0.x) + __uint_as_float(s0.y)) + (__uint_as_float(s0.z) + __uint_as_float(s0.w))) +
                              ((__uint_as_float(s1.x) + __uint_as_float(s1.y)) + (__uint_as_float(s1.z) + __uint_as_float(s1.w))) + (s2x + s2y)) * (1.0f / 640.0f);
            const float tot = ((__uint_as_float(u0.x) + __uint_as_float(u0.y)) + (__uint_as_float(u0.z) + __uint_as_float(u0.w))) +
                              ((__uint_as_float(u1.x) + __uint_as_float(u1.y)) + (__uint_as_float(u1.z) + __uint_as_float(u1.w))) + (u2x + u2y);
            const float so = __shfl_xor_sync(FULL, st, 1);
            const float cs = __shfl_xor_sync(FULL, tot, 16);
            const float mean = selp(st, so, lane_p & 1), msq = selp(so, st, lane_p & 1);
            const float var = fmaxf(fmaf(-mean, mean, msq), 0.f);
            const float rinv = fast_rcp(bfr(fast_sqrt(bfr(bfr(var) + 1e-5f))));
            const float z = fmaxf(fmaf(-bfr(mean), cs, tot) * rinv, 0.f);
            if (lane_p < 16) asm volatile("st.shared.u16 [%0], %1;" :: "r"(h1_w), "h"((unsigned short)pack_bf(z, 0.f)) : "memory");
            bar_arrive(NB_H1, 352);
        }
        if (f >= NOCT) return;
        mbar_wait(bars + BAR_CLR * 8);
        unsigned ha = ld_w1(hb0);
        bar_sync(NB_DSENT, 352);
        spin_cycles(dly_d);
        {
            uint4 v[7];
#pragma unroll
            for (int j = 0; j < 7; j++) v[j] = ld_w4(d_src + 128 * j);
#pragma unroll 1
            for (int n = 0; n < SPIN_LIMIT; n++) {
                if (!__any_sync(FULL, (ha & tag) == 0)) break;
                ha = ld_w1(hb0);
            }
            float hs = __uint_as_float(ha);
            hs += __shfl_xor_sync(FULL, hs, 8);
            hs += __shfl_xor_sync(FULL, hs, 16);
            const float base = bfr(xcol + bfr(hs));
            float r = 0.f;
#pragma unroll 1
            for (int n = 0; n < SPIN_LIMIT; n++) {
                float t0 = ((__uint_as_float(v[0].x) + __uint_as_float(v[1].x)) + (__uint_as_float(v[2].x) + __uint_as_float(v[3].x))) +
                           ((__uint_as_float(v[4].x) + __uint_as_float(v[5].x)) + __uint_as_float(v[6].x));
                float t1 = ((__uint_as_float(v[0].y) + __uint_as_float(v[1].y)) + (__uint_as_float(v[2].y) + __uint_as_float(v[3].y))) +
                           ((__uint_as_float(v[4].y) + __uint_as_float(v[5].y)) + __uint_as_float(v[6].y));
                float t2 = ((__uint_as_float(v[0].z) + __uint_as_float(v[1].z)) + (__uint_as_float(v[2].z) + __uint_as_float(v[3].z))) +
                           ((__uint_as_float(v[4].z) + __uint_as_float(v[5].z)) + __uint_as_float(v[6].z));
                float t3 = ((__uint_as_float(v[0].w) + __uint_as_float(v[1].w)) + (__uint_as_float(v[2].w) + __uint_as_float(v[3].w))) +
                           ((__uint_as_float(v[4].w) + __uint_as_float(v[5].w)) + __uint_as_float(v[6].w));
                asm volatile("" : "+f"(t0), "+f"(t1), "+f"(t2), "+f"(t3));
                bool miss = false;
#pragma unroll
                for (int j = 0; j < 7; j++)
                    if (bad4(v[j], tag)) { v[j] = ld_w4(d_src + 128 * j); miss = true; }
                const bool again = __any_sync(FULL, miss);
                r = octet_reduce(t0, t1, t2, t3, lane_p);
                if (!again) break;
            }
            if (lane_p < 8) asm volatile("st.global.u16 [%0], %1;" :: "l"(o_dst), "h"((unsigned short)pack_bf(base + bfr(r), 0.f)) : "memory");
            if (lane_p == 0) TL(13);
        }
        if (f == 0 && lane == 0) st_w1(scr + PR_EPOCH * PAIR_W, epoch + 1u);
    }
}

unsigned* g_scr_base = nullptr;
int g_w1_promo = 2;
int g_v_promo = 2;
int g_wo_promo = 2;

}

typedef CUresult (*EncodeTiledFn)(CUtensorMap*, CUtensorMapDataType, cuuint32_t, void*, const cuuint64_t*, const cuuint64_t*,
                                  const cuuint32_t*, const cuuint32_t*, CUtensorMapInterleave, CUtensorMapSwizzle,
                                  CUtensorMapL2promotion, CUtensorMapFloatOOBfill);

extern "C" void kernel_launch(void* const* d_in, const int* in_sizes, int n_in, void* d_out, int out_size) {
    (void)in_sizes; (void)n_in; (void)out_size;
    static EncodeTiledFn encode = nullptr;
    if (!encode) {
        cudaFuncSetAttribute(fk::fused_decode_kernel, cudaFuncAttributeMaxDynamicSharedMemorySize, fk::SMEM_BYTES);
        void* fn = nullptr;
        cudaDriverEntryPointQueryResult qres;
        cudaGetDriverEntryPoint("cuTensorMapEncodeTiled", &fn, cudaEnableDefault, &qres);
        encode = (EncodeTiledFn)fn;
        void* sp = nullptr;
        cudaGetSymbolAddress(&sp, fk::g_scr);
        fk::g_scr_base = (unsigned*)(((uintptr_t)sp + (2u << 20) - 1) & ~(uintptr_t)((2u << 20) - 1));
    }
    CUtensorMap map_v, map_w1, map_wo;
    {
        const cuuint64_t dims[2] = {640, 4096}, strides[1] = {1280};
        const cuuint32_t box[2] = {32, 64}, es[2] = {1, 1};
        encode(&map_wo, CU_TENSOR_MAP_DATA_TYPE_BFLOAT16, 2, d_in[4], dims, strides, box, es, CU_TENSOR_MAP_INTERLEAVE_NONE,
               CU_TENSOR_MAP_SWIZZLE_64B, (CUtensorMapL2promotion)fk::g_wo_promo, CU_TENSOR_MAP_FLOAT_OOB_FILL_NONE);
    }
    {
        const cuuint64_t dims[2] = {128, 32 * 4096}, strides[1] = {256};
        const cuuint32_t box[2] = {32, 64}, es[2] = {1, 1};
        encode(&map_v, CU_TENSOR_MAP_DATA_TYPE_BFLOAT16, 2, d_in[2], dims, strides, box, es, CU_TENSOR_MAP_INTERLEAVE_NONE,
               CU_TENSOR_MAP_SWIZZLE_64B, (CUtensorMapL2promotion)fk::g_v_promo, CU_TENSOR_MAP_FLOAT_OOB_FILL_NONE);
    }
    {
        const cuuint64_t dims[2] = {1728, 640}, strides[1] = {3456};
        const cuuint32_t box[2] = {16, 128}, es[2] = {1, 1};
        encode(&map_w1, CU_TENSOR_MAP_DATA_TYPE_BFLOAT16, 2, d_in[6], dims, strides, box, es, CU_TENSOR_MAP_INTERLEAVE_NONE,
               CU_TENSOR_MAP_SWIZZLE_32B, (CUtensorMapL2promotion)fk::g_w1_promo, CU_TENSOR_MAP_FLOAT_OOB_FILL_NONE);
    }
    fk::fused_decode_kernel<<<fk::NCTA, fk::NTHREADS, fk::SMEM_BYTES>>>(
        (const __nv_bfloat16*)d_in[0], (const __nv_bfloat16*)d_in[3], (const __nv_bfloat16*)d_in[1],
        (const __nv_bfloat16*)d_in[7], (__nv_bfloat16*)d_out, fk::g_scr_base,
        map_v, map_w1, map_wo);
}
```

```cpp
#include <cuda_runtime.h>
#include <cuda.h>
#include <cuda_bf16.h>
#include <stdint.h>

namespace fk {

constexpr int NCTA = 128;
constexpr int NFFN = 108;
constexpr int NOCT = 80;
constexpr int NWO = 80;
constexpr int NTHREADS = 384;

constexpr int ROW_PITCH = 1296;
constexpr int SM_K = 0;
constexpr int SM_V = 65536;
constexpr int SM_W1 = 131072;
constexpr int SM_W2 = SM_W1 + 640 * 32;
constexpr int SM_QPART = SM_W2 + 16 * ROW_PITCH;
constexpr int SM_P = SM_QPART + 4096;
constexpr int SM_XN = SM_P + 2048;
constexpr int SM_OPART = SM_XN + 2560;
constexpr int SM_ML = SM_OPART + 1024;
constexpr int SM_QS = SM_ML + 64;
constexpr int SM_HP = SM_QS + 256;
constexpr int SM_DP = SM_HP + 32 * 48;
constexpr int SM_H1 = SM_DP + 34 * 48;
constexpr int SM_OF = SM_H1 + 32;
constexpr int SM_TAG = SM_OF + 16 * 144;
constexpr int SM_BAR = SM_TAG + 32;
constexpr int BAR_K = 0, BAR_V = 16, BAR_WO = 32, BAR_W1 = 40, BAR_W2 = 45, BAR_SIDE = 46, BAR_CLR = 47, BAR_KFREE = 48, BAR_O = 49, BAR_HS = 50, NBAR = 51;
constexpr int SMEM_BYTES = SM_BAR + NBAR * 8;

constexpr int SPIN_LIMIT = 1 << 17;
constexpr int NPRE = 5;

struct Pace {
    int tK;
    int dKV;
    int dWO;
    int dW1;
    int dW2;
    int stag;
    int gap;
    int dlyD;
    int dlyO;
    int nprobe;
    int tP;
    int sV;
    int dV;
};
#define PACE_DEFAULT {1150, 160, 105, 120, 100, 20, 215, 330, 600, 8, 600, 4, 166}

__device__ __align__(4096) unsigned g_scr[1 << 20];
constexpr int PAIR_W = 2048, REP_W = 1024;
constexpr int PR_D = 0;
constexpr int PR_H = 172;
constexpr int PR_O = 84;
constexpr int PR_S = 88;
constexpr int PR_A = 120;
constexpr int PR_SIDE = 136;
constexpr int PR_PROBE = 137;
constexpr int PR_EPOCH = 169;
__device__ __forceinline__ int near_off(int pair, unsigned side) {
    return pair * PAIR_W + (int)((side ^ __popc((2 * pair) & 0xb3)) & 1u) * REP_W;
}

__device__ __forceinline__ unsigned gtime32() {
    unsigned long long t; asm volatile("mov.u64 %0, %globaltimer;" : "=l"(t) :: "memory"); return (unsigned)t;
}
__device__ __forceinline__ uint32_t smem_u32(const void* p) { return (uint32_t)__cvta_generic_to_shared(p); }
__device__ __forceinline__ void mbar_init(uint32_t bar, uint32_t cnt) {
    asm volatile("mbarrier.init.shared::cta.b64 [%0], %1;" :: "r"(bar), "r"(cnt) : "memory");
}
__device__ __forceinline__ void mbar_expect_tx(uint32_t bar, uint32_t bytes) {
    asm volatile("mbarrier.arrive.expect_tx.shared::cta.b64 _, [%0], %1;" :: "r"(bar), "r"(bytes) : "memory");
}
__device__ __forceinline__ void mbar_arrive(uint32_t bar) {
    asm volatile("mbarrier.arrive.shared::cta.b64 _, [%0];" :: "r"(bar) : "memory");
}
__device__ __forceinline__ bool mbar_test(uint32_t bar) {
    uint32_t ok;
    asm volatile("{\n.reg .pred p;\nmbarrier.test_wait.parity.shared::cta.b64 p, [%1], 0;\nselp.u32 %0, 1, 0, p;\n}"
                 : "=r"(ok) : "r"(bar) : "memory");
    return ok != 0;
}
__device__ __forceinline__ bool mbar_try(uint32_t bar) {
    uint32_t ok;
    asm volatile("{\n.reg .pred p;\nmbarrier.try_wait.parity.shared::cta.b64 p, [%1], 0;\nselp.u32 %0, 1, 0, p;\n}"
                 : "=r"(ok) : "r"(bar) : "memory");
    return ok != 0;
}
__device__ __forceinline__ void mbar_wait(uint32_t bar) {
#pragma unroll 1
    for (int n = 0; n < SPIN_LIMIT; n++) if (mbar_try(bar)) break;
}
__device__ __forceinline__ uint64_t stream_policy() {
    uint64_t p; asm volatile("createpolicy.fractional.L2::evict_first.b64 %0, 1.0;" : "=l"(p)); return p;
}
__device__ __forceinline__ void bulk_g2s(uint32_t dst, const void* src, uint32_t bytes, uint32_t bar, uint64_t pol) {
    asm volatile("cp.async.bulk.shared::cluster.global.mbarrier::complete_tx::bytes.L2::cache_hint [%0], [%1], %2, [%3], %4;"
                 :: "r"(dst), "l"(src), "r"(bytes), "r"(bar), "l"(pol) : "memory");
}
__device__ __forceinline__ void tma2d(uint32_t dst, const CUtensorMap* map, int c0, int c1, uint32_t bar, uint64_t pol) {
    asm volatile("cp.async.bulk.tensor.2d.shared::cluster.global.mbarrier::complete_tx::bytes.L2::cache_hint [%0], [%1, {%3, %4}], [%2], %5;"
                 :: "r"(dst), "l"(map), "r"(bar), "r"(c0), "r"(c1), "l"(pol) : "memory");
}
__device__ __forceinline__ unsigned tagw(float v, unsigned tag) { return (__float_as_uint(v) & ~3u) | tag; }
__device__ __forceinline__ float untag(unsigned w) { return __uint_as_float(w & ~3u); }
__device__ __forceinline__ void st_w1(unsigned* p, unsigned a) {
    asm volatile("st.relaxed.gpu.global.u32 [%0], %1;" :: "l"(p), "r"(a) : "memory");
}
__device__ __forceinline__ void st_w4(unsigned* p, uint4 v) {
    asm volatile("st.relaxed.gpu.global.v4.u32 [%0], {%1,%2,%3,%4};" :: "l"(p), "r"(v.x), "r"(v.y), "r"(v.z), "r"(v.w) : "memory");
}
__device__ __forceinline__ unsigned ld_w1(const unsigned* p) {
    unsigned v;
    asm volatile("ld.relaxed.gpu.global.u32 %0, [%1];" : "=r"(v) : "l"(p) : "memory");
    return v;
}
__device__ __forceinline__ uint4 ld_w4(const unsigned* p) {
    uint4 v;
    asm volatile("ld.relaxed.gpu.global.v4.u32 {%0,%1,%2,%3}, [%4];" : "=r"(v.x), "=r"(v.y), "=r"(v.z), "=r"(v.w) : "l"(p) : "memory");
    return v;
}
__device__ __forceinline__ uint2 ld_w2(const unsigned* p) {
    uint2 v;
    asm volatile("ld.relaxed.gpu.global.v2.u32 {%0,%1}, [%2];" : "=r"(v.x), "=r"(v.y) : "l"(p) : "memory");
    return v;
}
__device__ __forceinline__ bool bad2(uint2 v, unsigned tag) { return (v.x & v.y & tag) == 0; }
__device__ __forceinline__ bool bad4(uint4 v, unsigned tag) { return ((v.x & v.y & v.z) & v.w & tag) == 0; }

__device__ __forceinline__ void bar_sync(int id, int n) { __syncwarp(); asm volatile("bar.sync %0, %1;" :: "r"(id), "r"(n) : "memory"); }
__device__ __forceinline__ void bar_arrive(int id, int n) { __syncwarp(); asm volatile("bar.arrive %0, %1;" :: "r"(id), "r"(n) : "memory"); }
__device__ __forceinline__ void sts_p(uint32_t a, float v, unsigned p) {
    asm volatile("{\n.reg .pred p;\nsetp.ne.u32 p, %2, 0;\n@p st.shared.f32 [%0], %1;\n}" :: "r"(a), "f"(v), "r"(p) : "memory");
}
__device__ __forceinline__ float bf_lo(unsigned u) { return __uint_as_float(u << 16); }
__device__ __forceinline__ float bf_hi(unsigned u) { return __uint_as_float(u & 0xffff0000u); }
__device__ __forceinline__ unsigned pack_bf(float lo, float hi) {
    unsigned r; asm("cvt.rn.bf16x2.f32 %0, %1, %2;" : "=r"(r) : "f"(hi), "f"(lo)); return r;
}
__device__ __forceinline__ float bfr(float v) { return __uint_as_float(pack_bf(0.f, v)); }
__device__ __forceinline__ float selp(float a, float b, unsigned c) {
    float r; asm("{\n.reg .pred p;\nsetp.ne.u32 p, %3, 0;\nselp.f32 %0, %1, %2, p;\n}" : "=f"(r) : "f"(a), "f"(b), "r"(c)); return r;
}
__device__ __forceinline__ float sel4(float a0, float a1, float a2, float a3, int t) {
    return selp(selp(a3, a2, t & 1), selp(a1, a0, t & 1), t & 2);
}
__device__ __forceinline__ float fast_sqrt(float v) { float r; asm("sqrt.approx.ftz.f32 %0, %1;" : "=f"(r) : "f"(v)); return r; }
__device__ __forceinline__ float fast_rcp(float v) { float r; asm("rcp.approx.ftz.f32 %0, %1;" : "=f"(r) : "f"(v)); return r; }
template <class T> __device__ __forceinline__ T* pin(T* p) { asm volatile("" : "+l"(p)); return p; }
__device__ __forceinline__ void mma16816(float (&c)[4], unsigned a0, unsigned a1, unsigned a2, unsigned a3,
                                         unsigned b0, unsigned b1) {
    asm volatile("mma.sync.aligned.m16n8k16.row.col.f32.bf16.bf16.f32 {%0,%1,%2,%3}, {%4,%5,%6,%7}, {%8,%9}, {%0,%1,%2,%3};"
                 : "+f"(c[0]), "+f"(c[1]), "+f"(c[2]), "+f"(c[3])
                 : "r"(a0), "r"(a1), "r"(a2), "r"(a3), "r"(b0), "r"(b1));
}
__device__ __forceinline__ uint4 ldsm4t(uint32_t addr) {
    uint4 r;
    asm volatile("ldmatrix.sync.aligned.m8n8.x4.trans.shared.b16 {%0,%1,%2,%3}, [%4];"
                 : "=r"(r.x), "=r"(r.y), "=r"(r.z), "=r"(r.w) : "r"(addr) : "memory");
    return r;
}
__device__ __forceinline__ uint4 lds16(uint32_t addr) {
    uint4 r;
    asm volatile("ld.shared.v4.u32 {%0,%1,%2,%3}, [%4];" : "=r"(r.x), "=r"(r.y), "=r"(r.z), "=r"(r.w) : "r"(addr) : "memory");
    return r;
}
__device__ __forceinline__ void wait_until(unsigned t0, int t) {
#pragma unroll 1
    for (int n = 0; n < SPIN_LIMIT; n++) if ((int)(gtime32() - t0) >= t) break;
}
__device__ __forceinline__ void spin_cycles(int n) {
    if (n > 0) { const unsigned c0 = clock(); while ((int)(clock() - c0) < n) {} }
}
__device__ __forceinline__ float octet_reduce(float v0, float v1, float v2, float v3, int lane) {
    const unsigned FULL = 0xffffffffu;
    const unsigned b1 = lane & 2, b2 = lane & 4;
    float k0 = selp(v2, v0, b1), k1 = selp(v3, v1, b1);
    const float s0 = selp(v0, v2, b1), s1 = selp(v1, v3, b1);
    k0 += __shfl_xor_sync(FULL, s0, 2);
    k1 += __shfl_xor_sync(FULL, s1, 2);
    float k = selp(k1, k0, b2);
    const float s = selp(k0, k1, b2);
    k += __shfl_xor_sync(FULL, s, 4);
    k += __shfl_xor_sync(FULL, k, 8);
    k += __shfl_xor_sync(FULL, k, 16);
    return k;
}

constexpr int NB_XN = 1, NB_QPART = 2, NB_Q = 3, NB_OPART = 4, NB_FPART = 5, NB_DSENT = 6, NB_H1 = 7, NB_PROBE = 8, NB_TAG0 = 9, NB_TAG1 = 10, NB_HP = 11, NB_ML = 12;
constexpr int N_XN = NTHREADS - 64;

__global__ void __launch_bounds__(NTHREADS, 1)
fused_decode_kernel(const __nv_bfloat16* __restrict__ x, const __nv_bfloat16* __restrict__ wq,
                    const __nv_bfloat16* __restrict__ kc,
                    const __nv_bfloat16* __restrict__ w2, __nv_bfloat16* __restrict__ out, unsigned* __restrict__ scr,
                    const __grid_constant__ CUtensorMap map_v, const __grid_constant__ CUtensorMap map_w1,
                    const __grid_constant__ CUtensorMap map_wo) {
    constexpr Pace pc = PACE_DEFAULT;
    extern __shared__ __align__(1024) unsigned char smem[];
    const unsigned tstart = gtime32();
    const int tid = threadIdx.x, warp = tid >> 5, lane = tid & 31;
    const int b = blockIdx.x, h = b >> 2, c = b & 3;
    const int cw = warp - 2, ct = tid - 64;

    uint2 xr[5];
    unsigned epoch;
    uint4 wr[10];
    {
        const char* wp = reinterpret_cast<const char*>(wq) + (size_t)(160 * c + (ct >> 4)) * 8192 + h * 256 + (ct & 15) * 16;
        const uint2* xp = reinterpret_cast<const uint2*>(x) + lane;
        asm volatile("{\n.reg .pred p;\nsetp.ne.u32 p, %13, 0;\n@p bra.uni XSKIP;\n"
                     "ld.global.nc.v2.u32 {%0,%1}, [%11];\nld.global.nc.v2.u32 {%2,%3}, [%11+256];\nld.global.nc.v2.u32 {%4,%5}, [%11+512];\n"
                     "ld.global.nc.v2.u32 {%6,%7}, [%11+768];\nld.global.nc.v2.u32 {%8,%9}, [%11+1024];\n"
                     "ld.relaxed.gpu.global.u32 %10, [%12];\nXSKIP:\n}"
                     : "=r"(xr[0].x), "=r"(xr[0].y), "=r"(xr[1].x), "=r"(xr[1].y), "=r"(xr[2].x), "=r"(xr[2].y), "=r"(xr[3].x), "=r"(xr[3].y),
                       "=r"(xr[4].x), "=r"(xr[4].y), "=r"(epoch)
                     : "l"(xp), "l"(scr + PR_EPOCH * PAIR_W), "r"(warp) : "memory");
        asm volatile("{\n.reg .pred p;\nsetp.ge.u32 p, %41, 8;\n@p bra.uni WSKIP;\n"
                     "ld.global.nc.L1::no_allocate.v4.u32 {%0,%1,%2,%3}, [%40];\n"
                     "ld.global.nc.L1::no_allocate.v4.u32 {%4,%5,%6,%7}, [%40+131072];\n"
                     "ld.global.nc.L1::no_allocate.v4.u32 {%8,%9,%10,%11}, [%40+262144];\n"
                     "ld.global.nc.L1::no_allocate.v4.u32 {%12,%13,%14,%15}, [%40+393216];\n"
                     "ld.global.nc.L1::no_allocate.v4.u32 {%16,%17,%18,%19}, [%40+524288];\n"
                     "ld.global.nc.L1::no_allocate.v4.u32 {%20,%21,%22,%23}, [%40+655360];\n"
                     "ld.global.nc.L1::no_allocate.v4.u32 {%24,%25,%26,%27}, [%40+786432];\n"
                     "ld.global.nc.L1::no_allocate.v4.u32 {%28,%29,%30,%31}, [%40+917504];\n"
                     "ld.global.nc.L1::no_allocate.v4.u32 {%32,%33,%34,%35}, [%40+1048576];\n"
                     "ld.global.nc.L1::no_allocate.v4.u32 {%36,%37,%38,%39}, [%40+1179648];\n"
                     "WSKIP:\n}"
                     : "=r"(wr[0].x), "=r"(wr[0].y), "=r"(wr[0].z), "=r"(wr[0].w), "=r"(wr[1].x), "=r"(wr[1].y), "=r"(wr[1].z), "=r"(wr[1].w),
                       "=r"(wr[2].x), "=r"(wr[2].y), "=r"(wr[2].z), "=r"(wr[2].w), "=r"(wr[3].x), "=r"(wr[3].y), "=r"(wr[3].z), "=r"(wr[3].w),
                       "=r"(wr[4].x), "=r"(wr[4].y), "=r"(wr[4].z), "=r"(wr[4].w), "=r"(wr[5].x), "=r"(wr[5].y), "=r"(wr[5].z), "=r"(wr[5].w),
                       "=r"(wr[6].x), "=r"(wr[6].y), "=r"(wr[6].z), "=r"(wr[6].w), "=r"(wr[7].x), "=r"(wr[7].y), "=r"(wr[7].z), "=r"(wr[7].w),
                       "=r"(wr[8].x), "=r"(wr[8].y), "=r"(wr[8].z), "=r"(wr[8].w), "=r"(wr[9].x), "=r"(wr[9].y), "=r"(wr[9].z), "=r"(wr[9].w)
                     : "l"(wp), "r"(cw));
    }

    const uint32_t sb = smem_u32(smem);
    const uint32_t bars = sb + SM_BAR;
    const int g = lane >> 2, t = lane & 3;
    const unsigned FULL = 0xffffffffu;
    volatile unsigned* const misc = reinterpret_cast<volatile unsigned*>(smem + SM_TAG);
    const int f = (b >= NWO) ? b - NWO : b + (NCTA - NWO);

    auto ktile = [&](int i) { return 16 * c + ((i + b) & 15); };
    auto vchunk = [&](int i) { return (i + (h >> 1)) & 15; };

    if ((unsigned)cw < 10u) {
        const int mi = lane >> 3, ri = lane & 7;
        unsigned tag, side, sd0, sd1;
        const int oct = 2 * (4 * cw + t);
        const unsigned xpair = __ldg(reinterpret_cast<const unsigned*>(x) + ct);
        if (cw < 8) {
            bar_sync(NB_XN, N_XN);
            tag = misc[0];
            unsigned* const s_dst = scr + (PR_S + h) * PAIR_W + ktile(cw + 8 * (t >> 1)) * 16 + 8 * (t & 1) + g;
            st_w1(s_dst, 0u); st_w1(s_dst + REP_W, 0u);
            {
                const float* xn = reinterpret_cast<const float*>(smem + SM_XN) + 160 * c + (ct >> 4);
                float acc[8];
#pragma unroll
                for (int j = 0; j < 8; j++) acc[j] = 0.f;
#pragma unroll
                for (int i = 0; i < 10; i++) {
                    const float xv = xn[16 * i];
                    acc[0] = fmaf(xv, bf_lo(wr[i].x), acc[0]); acc[1] = fmaf(xv, bf_hi(wr[i].x), acc[1]);
                    acc[2] = fmaf(xv, bf_lo(wr[i].y), acc[2]); acc[3] = fmaf(xv, bf_hi(wr[i].y), acc[3]);
                    acc[4] = fmaf(xv, bf_lo(wr[i].z), acc[4]); acc[5] = fmaf(xv, bf_hi(wr[i].z), acc[5]);
                    acc[6] = fmaf(xv, bf_lo(wr[i].w), acc[6]); acc[7] = fmaf(xv, bf_hi(wr[i].w), acc[7]);
                }
#pragma unroll
                for (int j = 0; j < 8; j++) acc[j] += __shfl_xor_sync(FULL, acc[j], 16);
                if (lane < 16) {
                    float4* qp = reinterpret_cast<float4*>(smem + SM_QPART + cw * 512 + lane * 32);
                    qp[0] = make_float4(acc[0], acc[1], acc[2], acc[3]);
                    qp[1] = make_float4(acc[4], acc[5], acc[6], acc[7]);
                }
            }
            bar_arrive(NB_QPART, 288);
            bar_sync(NB_Q, 288);
            uint4 qf[4];
#pragma unroll
            for (int j = 0; j < 4; j++) qf[j] = lds16(sb + SM_QS + 16 * (t + 4 * (j ^ (g & 1))));
            float mys = 0.f;
#pragma unroll 1
            for (int tile = 0; tile < 2; tile++) {
                const int ch = cw + 8 * tile;
                mbar_wait(bars + (BAR_K + ch) * 8);
                const uint32_t kb = sb + SM_K + ch * 4096 + g * 256 + t * 16;
                float cA[4] = {0.f, 0.f, 0.f, 0.f}, cB[4] = {0.f, 0.f, 0.f, 0.f};
#pragma unroll
                for (int j = 0; j < 4; j++) {
                    const uint32_t a = kb + 64 * (j ^ (g & 1));
                    const uint4 ra = lds16(a), rb = lds16(a + 2048);
                    mma16816(cA, ra.x, rb.x, ra.y, rb.y, qf[j].x, qf[j].y);
                    mma16816(cB, ra.z, rb.z, ra.w, rb.w, qf[j].z, qf[j].w);
                }
                const float s0 = selp(cA[1] + cB[1], cA[0] + cB[0], g & 1);
                const float s1 = selp(cA[3] + cB[3], cA[2] + cB[2], g & 1);
                mys = selp(selp(s1, s0, t & 1), mys, (t >> 1) == tile);
            }
            __syncwarp();
            if (lane == 0) mbar_arrive(bars + BAR_KFREE * 8);
            mys = bfr(bfr(mys) * 0.08838834764831845f);
            st_w1(s_dst, __float_as_uint(mys) | tag);
            st_w1(s_dst + REP_W, __float_as_uint(mys) | tag);
            {
                mbar_wait(bars + (BAR_V + pc.sV) * 8);
                mbar_wait(bars + BAR_SIDE * 8);
                const unsigned* ps = scr + near_off(PR_S + h, misc[1]) + vchunk(cw + 8 * (lane >> 4)) * 64 + 4 * (lane & 15);
                uint4 v = ld_w4(ps);
#pragma unroll 1
                for (int n = 0; n < SPIN_LIMIT; n++) {
                    if (!__any_sync(FULL, bad4(v, tag))) break;
                    __nanosleep(50);
                    v = ld_w4(ps);
                }
                const float e0 = untag(v.x), e1 = untag(v.y), e2 = untag(v.z), e3 = untag(v.w);
                float m = fmaxf(fmaxf(e0, e1), fmaxf(e2, e3));
#pragma unroll
                for (int o = 16; o; o >>= 1) m = fmaxf(m, __shfl_xor_sync(FULL, m, o));
                const unsigned p01 = pack_bf(__expf(e0 - m), __expf(e1 - m)), p23 = pack_bf(__expf(e2 - m), __expf(e3 - m));
                reinterpret_cast<uint2*>(smem + SM_P)[cw * 32 + lane] = make_uint2(p01, p23);
                float l = (bf_lo(p01) + bf_hi(p01)) + (bf_lo(p23) + bf_hi(p23));
#pragma unroll
                for (int o = 16; o; o >>= 1) l += __shfl_xor_sync(FULL, l, o);
                if (lane == 0) reinterpret_cast<float2*>(smem + SM_ML)[cw] = make_float2(m, l);
                bar_arrive(NB_ML, 288);
            }
            float o0[4] = {0.f, 0.f, 0.f, 0.f}, o1[4] = {0.f, 0.f, 0.f, 0.f};
            const int vrow = (mi >> 1) * 8 + ri;
            const uint32_t va0 = vrow * 64 + (((mi & 1) ^ ((ri >> 1) & 3)) * 16);
            const uint32_t va1 = vrow * 64 + (((2 + (mi & 1)) ^ ((ri >> 1) & 3)) * 16);
#pragma unroll 1
            for (int tile = 0; tile < 2; tile++) {
                const int ch = cw + 8 * tile;
                const unsigned* pp = reinterpret_cast<const unsigned*>(smem + SM_P) + cw * 64 + tile * 32 + t;
                unsigned pf[8];
#pragma unroll
                for (int s = 0; s < 8; s++) pf[s] = pp[4 * s];
                mbar_wait(bars + (BAR_V + ch) * 8);
                const uint32_t vb = sb + SM_V + ch * 4096;
#pragma unroll
                for (int s = 0; s < 4; s++) {
                    const uint4 a0 = ldsm4t(vb + s * 1024 + va0), a1 = ldsm4t(vb + s * 1024 + va1);
                    mma16816(o0, a0.x, a0.y, a0.z, a0.w, pf[2 * s], pf[2 * s + 1]);
                    mma16816(o1, a1.x, a1.y, a1.z, a1.w, pf[2 * s], pf[2 * s + 1]);
                }
            }
            reinterpret_cast<float*>(smem + SM_OPART)[cw * 32 + 8 * t + g] = sel4(o0[0], o0[2], o1[0], o1[2], t);
            bar_arrive(NB_OPART, 288);
            side = misc[1];
            sd0 = ld_w1(scr + near_off(PR_SIDE, side) + oct * 8); sd1 = ld_w1(scr + near_off(PR_SIDE, side) + oct * 8 + 8);
            if (b < NWO) {
                const int ks = cw >> 1;
                const uint32_t ab = sb + SM_K + (cw & 1) * 4096 + (16 * ks + (mi >> 1) * 8 + ri) * 64;
                const uint32_t ab0 = ab + (((mi & 1) ^ ((ri >> 1) & 3)) * 16), ab1 = ab + (((2 + (mi & 1)) ^ ((ri >> 1) & 3)) * 16);
                uint4 a[2 * NPRE];
#pragma unroll
                for (int i = 0; i < NPRE; i++) {
                    mbar_wait(bars + (BAR_WO + i) * 8);
                    a[2 * i] = ldsm4t(ab0 + i * 8192); a[2 * i + 1] = ldsm4t(ab1 + i * 8192);
                }
                mbar_wait(bars + BAR_O * 8);
                uint4 bf[4];
#pragma unroll
                for (int i = 0; i < 4; i++) bf[i] = lds16(sb + SM_OF + (ks * 4 + t) * 144 + (cw & 1) * 64 + i * 16);
                float cc[4][4];
#pragma unroll
                for (int i = 0; i < 4; i++) cc[i][0] = cc[i][1] = cc[i][2] = cc[i][3] = 0.f;
#pragma unroll
                for (int i = 0; i < 8; i++) {
                    uint4 a0, a1;
                    if (i < NPRE) { a0 = a[2 * i]; a1 = a[2 * i + 1]; }
                    else {
                        mbar_wait(bars + (BAR_WO + i) * 8);
                        a0 = ldsm4t(ab0 + i * 8192); a1 = ldsm4t(ab1 + i * 8192);
                    }
                    const unsigned b0 = (i & 1) ? bf[i >> 1].z : bf[i >> 1].x, b1 = (i & 1) ? bf[i >> 1].w : bf[i >> 1].y;
                    mma16816(cc[2 * (i & 1)], a0.x, a0.y, a0.z, a0.w, b0, b1);
                    mma16816(cc[2 * (i & 1) + 1], a1.x, a1.y, a1.z, a1.w, b0, b1);
                }
                sts_p(sb + SM_HP + ((8 * t + g) * 12 + cw) * 4,
                      sel4(cc[0][0] + cc[2][0], cc[0][2] + cc[2][2], cc[1][0] + cc[3][0], cc[1][2] + cc[3][2], t), 1u);
                bar_arrive(NB_HP, 288);
            }
        } else {
            unsigned* const probe = scr + near_off(PR_PROBE + (b >> 2), cw & 1) + (b & 3) * 256;
            st_w1(probe + (lane >> 3) * 32 + (lane & 7), 0u);
            st_w1(probe + 128 + (lane >> 3) * 32 + (lane & 7), 0u);
            if (cw == 8 && lane == 0) misc[2] = 0u;
            wait_until(tstart, pc.tP);
            bar_sync(NB_PROBE, 64);
            unsigned v = 0;
#pragma unroll 1
            for (int i = 0; i < pc.nprobe; i++) v = ld_w1(probe + i * 32 + v);
            unsigned won = 0;
            if (lane == 0) won = (atomicExch(reinterpret_cast<unsigned*>(smem + SM_TAG) + 2, 1u + v) == 0u);
            won = __shfl_sync(FULL, won, 0);
            if (cw & 1) bar_sync(NB_TAG1, 64); else bar_sync(NB_TAG0, 64);
            tag = misc[0];
            if (won) {
                const unsigned sd = cw & 1;
                if (lane == 0) {
                    misc[1] = sd;
                    mbar_arrive(bars + BAR_SIDE * 8);
                }
                if (f < NOCT) {
                    unsigned* i1 = scr + near_off(PR_D + f, sd) + 4 * lane;
#pragma unroll
                    for (int j = 0; j < 7; j++) {
                        const unsigned z = (j * 16 + (lane >> 1) >= NFFN) ? tag : 0u;
                        st_w4(i1 + 128 * j, make_uint4(z, z, z, z));
                    }
                    asm volatile("fence.acq_rel.gpu;" ::: "memory");
                    __syncwarp();
                    if (lane < 16) st_w1(scr + PR_SIDE * PAIR_W + (lane >> 3) * REP_W + f * 8 + (lane & 7), (sd << 2) | tag);
                    if (lane == 0) { mbar_arrive(bars + BAR_CLR * 8); }
                }
            }
            mbar_wait(bars + (BAR_V + 15) * 8);
            mbar_wait(bars + BAR_SIDE * 8);
            side = misc[1];
            sd0 = ld_w1(scr + near_off(PR_SIDE, side) + oct * 8); sd1 = ld_w1(scr + near_off(PR_SIDE, side) + oct * 8 + 8);
            if (b < NWO) {
                const unsigned* po = scr + near_off(PR_O + b / 20, side) + (cw & 1) * 512 + 4 * lane;
                unsigned* of = reinterpret_cast<unsigned*>(smem + SM_OF) + (((lane >> 2) & 3) * 4 + 2 * (lane & 1)) * 36 +
                               (lane >> 4) * 16 + 8 * (cw & 1) + ((lane >> 1) & 1);
                spin_cycles(pc.dlyO);
                uint4 ov[4];
#pragma unroll
                for (int q = 0; q < 4; q++) ov[q] = ld_w4(po + 128 * q);
#pragma unroll 1
                for (int n = 0; n < SPIN_LIMIT; n++) {
                    bool miss = false;
#pragma unroll
                    for (int q = 0; q < 4; q++) if (bad4(ov[q], tag)) { ov[q] = ld_w4(po + 128 * q); miss = true; }
                    if (!__any_sync(FULL, miss)) break;
                }
#pragma unroll
                for (int q = 0; q < 4; q++) {
                    of[2 * q] = __byte_perm(ov[q].x, ov[q].y, 0x7632);
                    of[2 * q + 36] = __byte_perm(ov[q].z, ov[q].w, 0x7632);
                }
                __syncwarp();
                if (lane == 0) { mbar_arrive(bars + BAR_O * 8); }
            }
        }
        if (f >= NFFN) return;

        const unsigned* const sd_src = scr + near_off(PR_SIDE, side) + oct * 8;
        const unsigned* const h_src0 = pin(scr + near_off(PR_H, side) + 2 * ct);
        const unsigned* const h_src1 = pin(scr + near_off(PR_H + 1, side) + 2 * ct);
        const unsigned* const h_src2 = pin(scr + near_off(PR_H + 2, side) + 2 * ct);
        const unsigned* const h_src3 = pin(scr + near_off(PR_H + 3, side) + 2 * ct);
#pragma unroll 1
        for (int n = 0; n < SPIN_LIMIT; n++) {
            if (!__any_sync(FULL, (sd0 & sd1 & tag) == 0)) break;
            __nanosleep(100);
            sd0 = ld_w1(sd_src); sd1 = ld_w1(sd_src + 8);
        }
        unsigned* const d_a = pin(scr + near_off(PR_D + oct, sd0 >> 2) + f * 8 + g);
        unsigned* const d_b = pin(scr + near_off(PR_D + oct + 1, sd1 >> 2) + f * 8 + g);
        uint32_t dp_w = sb + SM_DP + ((g + 8 * t) * 12 + cw) * 4;
        uint32_t st_w = sb + SM_DP + ((32 + lane) * 12 + cw) * 4;
        uint32_t w2_r = sb + SM_W2 + ((mi >> 1) * 8 + ri) * ROW_PITCH + cw * 128 + (mi & 1) * 16;
        uint32_t w1_r = sb + SM_W1 + (64 * cw + (mi >> 1) * 8 + ri) * 32 + (((mi & 1) ^ (ri >> 2)) * 16);
        uint32_t w1_bar = bars + (BAR_W1 + (cw >> 1)) * 8;
        asm volatile("" : "+r"(dp_w), "+r"(st_w), "+r"(w2_r), "+r"(w1_r), "+r"(w1_bar));
        mbar_wait(bars + ((b < NWO) ? BAR_HS : BAR_W1) * 8);
        uint2 h0 = ld_w2(h_src0), h1 = ld_w2(h_src1), h2 = ld_w2(h_src2), h3 = ld_w2(h_src3);
        uint4 a[4];
        bool w1_in = false;
#pragma unroll 1
        for (int n = 0; n < SPIN_LIMIT; n++) {
            if (!w1_in && mbar_test(w1_bar)) {
                w1_in = true;
#pragma unroll
                for (int s = 0; s < 4; s++) a[s] = ldsm4t(w1_r + s * 512);
            }
            bool miss = false;
            if (bad2(h0, tag)) { h0 = ld_w2(h_src0); miss = true; }
            if (bad2(h1, tag)) { h1 = ld_w2(h_src1); miss = true; }
            if (bad2(h2, tag)) { h2 = ld_w2(h_src2); miss = true; }
            if (bad2(h3, tag)) { h3 = ld_w2(h_src3); miss = true; }
            if (!__any_sync(FULL, miss)) break;
        }
        const unsigned att = pack_bf((__uint_as_float(h0.x) + __uint_as_float(h1.x)) + (__uint_as_float(h2.x) + __uint_as_float(h3.x)),
                                     (__uint_as_float(h0.y) + __uint_as_float(h1.y)) + (__uint_as_float(h2.y) + __uint_as_float(h3.y)));
        const unsigned hpair = pack_bf(bf_lo(xpair) + bf_lo(att), bf_hi(xpair) + bf_hi(att));
        unsigned hf[8];
#pragma unroll
        for (int s = 0; s < 8; s++) hf[s] = __shfl_sync(FULL, hpair, 4 * s + t);
        {
            float sA[4] = {0.f, 0.f, 0.f, 0.f}, sB[4] = {0.f, 0.f, 0.f, 0.f};
#pragma unroll
            for (int s = 0; s < 4; s += 2) {
                mma16816(sA, hf[2 * s], 0x3F803F80u, hf[2 * s + 1], 0x3F803F80u, hf[2 * s], hf[2 * s + 1]);
                mma16816(sB, hf[2 * s + 2], 0x3F803F80u, hf[2 * s + 3], 0x3F803F80u, hf[2 * s + 2], hf[2 * s + 3]);
            }
            if (!w1_in) {
                mbar_wait(w1_bar);
#pragma unroll
                for (int s = 0; s < 4; s++) a[s] = ldsm4t(w1_r + s * 512);
            }
            float dA[4] = {0.f, 0.f, 0.f, 0.f}, dB[4] = {0.f, 0.f, 0.f, 0.f};
#pragma unroll
            for (int s = 0; s < 8; s++) hf[s] = (g < 4) ? hf[s] : 0x3F803F80u;
#pragma unroll
            for (int s = 0; s < 4; s += 2) {
                mma16816(dA, a[s].x, a[s].y, a[s].z, a[s].w, hf[2 * s], hf[2 * s + 1]);
                mma16816(dB, a[s + 1].x, a[s + 1].y, a[s + 1].z, a[s + 1].w, hf[2 * s + 2], hf[2 * s + 3]);
            }
            sts_p(st_w, selp(sA[2] + sB[2], sA[0] + sB[0], lane), lane < 2);
            sts_p(dp_w, selp(dA[2] + dB[2], dA[0] + dB[0], t & 1), 1u);
        }
        bar_arrive(NB_FPART, 352);
        uint4 w[4];
        mbar_wait(bars + BAR_W2 * 8);
#pragma unroll
        for (int j = 0; j < 4; j++) w[j] = ldsm4t(w2_r + j * 32);
        bar_sync(NB_H1, 352);
        unsigned b0, b1;
        asm volatile("ld.shared.u32 %0, [%1];" : "=r"(b0) : "r"(sb + SM_H1 + 4 * t) : "memory");
        asm volatile("ld.shared.u32 %0, [%1];" : "=r"(b1) : "r"(sb + SM_H1 + 16 + 4 * t) : "memory");
        float y[4][4];
#pragma unroll
        for (int j = 0; j < 4; j++) {
            y[j][0] = y[j][1] = y[j][2] = y[j][3] = 0.f;
            mma16816(y[j], w[j].x, w[j].y, w[j].z, w[j].w, b0, b1);
        }
        st_w1(d_a, tagw(sel4(y[0][0], y[1][0], y[2][0], y[3][0], t), tag));
        st_w1(d_b, tagw(sel4(y[0][2], y[1][2], y[2][2], y[3][2], t), tag));
        if (f < NOCT) bar_arrive(NB_DSENT, 352);
    } else if (warp == 1) {
        const unsigned t0 = tstart + (unsigned)((h & 7) * pc.stag);
        if (lane == 0) {
#pragma unroll
            for (int i = 0; i < BAR_KFREE; i++) mbar_init(bars + i * 8, 1);
            mbar_init(bars + BAR_KFREE * 8, 8);
            mbar_init(bars + BAR_O * 8, 2);
            mbar_init(bars + BAR_HS * 8, 1);
            asm volatile("fence.mbarrier_init.release.cluster;" ::: "memory");
            asm volatile("prefetch.tensormap [%0];" :: "l"(&map_v) : "memory");
            asm volatile("prefetch.tensormap [%0];" :: "l"(&map_w1) : "memory");
            asm volatile("prefetch.tensormap [%0];" :: "l"(&map_wo) : "memory");
        }
        bar_arrive(NB_XN, N_XN);
        if (lane == 0) {
            int tt = pc.tK;
            const uint64_t pol = stream_policy();
            const char* ks = reinterpret_cast<const char*>(kc) + (size_t)h * 1048576 + 786432;
#pragma unroll 1
            for (int i = 0; i < 16; i++) {
                wait_until(t0, tt); tt += pc.dKV;
                mbar_expect_tx(bars + (BAR_K + i) * 8, 4096);
                bulk_g2s(sb + SM_K + i * 4096, ks + ktile(i) * 4096, 4096, bars + (BAR_K + i) * 8, pol);
            }
#pragma unroll 1
            for (int i = 0; i < 16; i++) {
                wait_until(t0, tt); tt += pc.dV;
                mbar_expect_tx(bars + (BAR_V + i) * 8, 4096);
                tma2d(sb + SM_V + i * 4096, &map_v, 32 * c, h * 4096 + 3072 + 64 * vchunk(i), bars + (BAR_V + i) * 8, pol);
            }
            tt += 70 - (h & 7) * pc.stag;
            if (b < NWO) {
                const int c0 = 32 * (b % 20), r0 = 1024 * (b / 20);
                mbar_wait(bars + BAR_KFREE * 8);
#pragma unroll 1
                for (int i = 0; i < 16; i++) {
                    wait_until(t0, tt + i * pc.dWO);
                    if (!(i & 1)) mbar_expect_tx(bars + (BAR_WO + (i >> 1)) * 8, 8192);
                    tma2d(sb + SM_K + i * 4096, &map_wo, c0, r0 + 64 * i, bars + (BAR_WO + (i >> 1)) * 8, pol);
                }
            }
            tt += 16 * pc.dWO + pc.gap + (h & 7) * 15;
            if (f < NFFN) {
#pragma unroll 1
                for (int j = 0; j < 5; j++) {
                    wait_until(t0, tt); tt += pc.dW1;
                    mbar_expect_tx(bars + (BAR_W1 + j) * 8, 4096);
                    tma2d(sb + SM_W1 + j * 4096, &map_w1, 16 * f, 128 * j, bars + (BAR_W1 + j) * 8, pol);
                }
                const char* w2s = reinterpret_cast<const char*>(w2) + (size_t)f * 16 * 1280;
                mbar_expect_tx(bars + BAR_W2 * 8, 16 * 1280);
#pragma unroll 1
                for (int j = 0; j < 4; j++) {
                    wait_until(t0, tt); tt += pc.dW2;
#pragma unroll
                    for (int i = 0; i < 4; i++) {
                        const int r = j * 4 + i;
                        bulk_g2s(sb + SM_W2 + r * ROW_PITCH, w2s + r * 1280, 1280, bars + BAR_W2 * 8, pol);
                    }
                }
            }
        }
    } else {
        const int col = 8 * f + 4 * (lane & 1) + (lane & 2) + ((lane >> 2) & 1);
        float xcol = 0.f;
        if (f < NOCT) xcol = __bfloat162float(x[col]);
        {
            float s = 0.f;
#pragma unroll
            for (int j = 0; j < 5; j++) s += (bf_lo(xr[j].x) + bf_hi(xr[j].x)) + (bf_lo(xr[j].y) + bf_hi(xr[j].y));
#pragma unroll
            for (int o = 16; o; o >>= 1) s += __shfl_xor_sync(FULL, s, o);
            const float mean = s * (1.0f / 640.0f);
            float v = 0.f;
#pragma unroll
            for (int j = 0; j < 5; j++) {
                float d0 = bf_lo(xr[j].x) - mean, d1 = bf_hi(xr[j].x) - mean, d2 = bf_lo(xr[j].y) - mean, d3 = bf_hi(xr[j].y) - mean;
                v += (d0 * d0 + d1 * d1) + (d2 * d2 + d3 * d3);
            }
#pragma unroll
            for (int o = 16; o; o >>= 1) v += __shfl_xor_sync(FULL, v, o);
            const float mb = bfr(mean);
            const float rb = __frcp_rn(bfr(__fsqrt_rn(bfr(bfr(v * (1.0f / 640.0f)) + 1e-5f))));
            float4* xn = reinterpret_cast<float4*>(smem + SM_XN);
#pragma unroll
            for (int j = 0; j < 5; j++) {
                float4 o;
                o.x = bfr(bfr(bf_lo(xr[j].x) - mb) * rb); o.y = bfr(bfr(bf_hi(xr[j].x) - mb) * rb);
                o.z = bfr(bfr(bf_lo(xr[j].y) - mb) * rb); o.w = bfr(bfr(bf_hi(xr[j].y) - mb) * rb);
                xn[j * 32 + lane] = o;
            }
        }
        const unsigned tag = 1u + (epoch & 1u);
        if (lane == 0) misc[0] = tag;
        bar_sync(NB_XN, N_XN);
        bar_arrive(NB_TAG0, 64);
        bar_arrive(NB_TAG1, 64);
        unsigned* const a_dst = scr + (PR_A + (h >> 1)) * PAIR_W + (b & 7) * 128 + 4 * lane;
        unsigned* const h_dst = pin(scr + (PR_H + b / 20) * PAIR_W + 32 * (b % 20) + lane);
        unsigned* const o_msg = pin(scr + (PR_O + (b >> 5)) * PAIR_W + (b & 31) * 32 + lane);
        st_w1(o_msg, 0u); st_w1(o_msg + REP_W, 0u);
        st_w4(a_dst, make_uint4(0u, 0u, 0u, 0u));
        st_w4(a_dst + REP_W, make_uint4(0u, 0u, 0u, 0u));
        if (b < NWO) { st_w1(h_dst, 0u); st_w1(h_dst + REP_W, 0u); }
        bar_sync(NB_QPART, 288);
        {
            const float4* qp = reinterpret_cast<const float4*>(smem + SM_QPART) + lane;
            float4 s = qp[0];
#pragma unroll
            for (int w = 1; w < 8; w++) { const float4 u = qp[w * 32]; s.x += u.x; s.y += u.y; s.z += u.z; s.w += u.w; }
            const uint4 mine = make_uint4(tagw(s.x, tag), tagw(s.y, tag), tagw(s.z, tag), tagw(s.w, tag));
            st_w4(a_dst, mine);
            st_w4(a_dst + REP_W, mine);
            mbar_wait(bars + BAR_SIDE * 8);
            const unsigned* pa = scr + near_off(PR_A + (h >> 1), misc[1]) + (h & 1) * 512 + 4 * lane;
            uint4 v[4];
#pragma unroll 1
            for (int n = 0; n < SPIN_LIMIT; n++) {
#pragma unroll
                for (int cc = 0; cc < 4; cc++) v[cc] = (cc == c) ? mine : ld_w4(pa + cc * 128);
                if (!__any_sync(FULL, bad4(v[0], tag) | bad4(v[1], tag) | bad4(v[2], tag) | bad4(v[3], tag))) break;
                __nanosleep(50);
            }
            const float q0 = ((untag(v[0].x) + untag(v[1].x)) + untag(v[2].x)) + untag(v[3].x);
            const float q1 = ((untag(v[0].y) + untag(v[1].y)) + untag(v[2].y)) + untag(v[3].y);
            const float q2 = ((untag(v[0].z) + untag(v[1].z)) + untag(v[2].z)) + untag(v[3].z);
            const float q3 = ((untag(v[0].w) + untag(v[1].w)) + untag(v[2].w)) + untag(v[3].w);
            reinterpret_cast<uint2*>(smem + SM_QS)[lane] = make_uint2(pack_bf(q0, q1), pack_bf(q2, q3));
        }
        bar_arrive(NB_Q, 288);
        bar_sync(NB_ML, 288);
        {
            const float* op = reinterpret_cast<const float*>(smem + SM_OPART) + lane;
            const float4* ml = reinterpret_cast<const float4*>(smem + SM_ML);
            const float4 e0 = ml[0], e1 = ml[1], e2 = ml[2], e3 = ml[3];
            const float M = fmaxf(fmaxf(fmaxf(e0.x, e0.z), fmaxf(e1.x, e1.z)), fmaxf(fmaxf(e2.x, e2.z), fmaxf(e3.x, e3.z)));
            float f0 = __expf(e0.x - M), f1 = __expf(e0.z - M), f2 = __expf(e1.x - M), f3 = __expf(e1.z - M);
            float f4 = __expf(e2.x - M), f5 = __expf(e2.z - M), f6 = __expf(e3.x - M), f7 = __expf(e3.z - M);
            const float inv = fast_rcp(((f0 * e0.y + f1 * e0.w) + (f2 * e1.y + f3 * e1.w)) + ((f4 * e2.y + f5 * e2.w) + (f6 * e3.y + f7 * e3.w)));
            f0 *= inv; f1 *= inv; f2 *= inv; f3 *= inv; f4 *= inv; f5 *= inv; f6 *= inv; f7 *= inv;
            asm volatile("" : "+f"(f0), "+f"(f1), "+f"(f2), "+f"(f3), "+f"(f4), "+f"(f5), "+f"(f6), "+f"(f7));
            bar_sync(NB_OPART, 288);
            const float o = ((f0 * op[0] + f1 * op[32]) + (f2 * op[64] + f3 * op[96])) + ((f4 * op[128] + f5 * op[160]) + (f6 * op[192] + f7 * op[224]));
            const unsigned ow = __float_as_uint(bfr(o)) | tag;
            st_w1(o_msg, ow); st_w1(o_msg + REP_W, ow);
        }
        const unsigned side = misc[1];
        const unsigned* const d_src = pin(scr + near_off(PR_D + f, side) + 4 * lane);
        const unsigned* const hb0 = pin(scr + near_off(PR_H + (lane >> 3), side) + col);
        __nv_bfloat16* const o_dst = pin(out + col);
        int lane_p = lane, dly_d = pc.dlyD;
        uint32_t hp_r = sb + SM_HP + lane * 48;
        asm volatile("" : "+r"(lane_p), "+r"(dly_d), "+r"(hp_r));
        if (b < NWO) {
            bar_sync(NB_HP, 288);
            const uint4 u0 = lds16(hp_r), u1 = lds16(hp_r + 16);
            const unsigned hw = tagw(((__uint_as_float(u0.x) + __uint_as_float(u0.y)) + (__uint_as_float(u0.z) + __uint_as_float(u0.w))) +
                                     ((__uint_as_float(u1.x) + __uint_as_float(u1.y)) + (__uint_as_float(u1.z) + __uint_as_float(u1.w))), tag);
            st_w1(h_dst, hw); st_w1(h_dst + REP_W, hw);
            __syncwarp();
            if (lane_p == 0) mbar_arrive(bars + BAR_HS * 8);
        }
        if (f >= NFFN) return;
        {
            uint32_t dp_r = sb + SM_DP + lane * 48, st_r = sb + SM_DP + (32 + (lane & 1)) * 48, h1_w = sb + SM_H1 + 2 * lane;
            asm volatile("" : "+r"(dp_r), "+r"(st_r), "+r"(h1_w));
            bar_sync(NB_FPART, 352);
            const uint4 s0 = lds16(st_r), s1 = lds16(st_r + 16), u0 = lds16(dp_r), u1 = lds16(dp_r + 16);
            float s2x, s2y, u2x, u2y;
            asm volatile("ld.shared.v2.f32 {%0,%1}, [%2];" : "=f"(s2x), "=f"(s2y) : "r"(st_r + 32) : "memory");
            asm volatile("ld.shared.v2.f32 {%0,%1}, [%2];" : "=f"(u2x), "=f"(u2y) : "r"(dp_r + 32) : "memory");
            const float st = (((__uint_as_float(s0.x) + __uint_as_float(s0.y)) + (__uint_as_float(s0.z) + __uint_as_float(s0.w))) +
                              ((__uint_as_float(s1.x) + __uint_as_float(s1.y)) + (__uint_as_float(s1.z) + __uint_as_float(s1.w))) + (s2x + s2y)) * (1.0f / 640.0f);
            const float tot = ((__uint_as_float(u0.x) + __uint_as_float(u0.y)) + (__uint_as_float(u0.z) + __uint_as_float(u0.w))) +
                              ((__uint_as_float(u1.x) + __uint_as_float(u1.y)) + (__uint_as_float(u1.z) + __uint_as_float(u1.w))) + (u2x + u2y);
            const float so = __shfl_xor_sync(FULL, st, 1);
            const float cs = __shfl_xor_sync(FULL, tot, 16);
            const float mean = selp(st, so, lane_p & 1), msq = selp(so, st, lane_p & 1);
            const float var = fmaxf(fmaf(-mean, mean, msq), 0.f);
            const float rinv = fast_rcp(bfr(fast_sqrt(bfr(bfr(var) + 1e-5f))));
            const float z = fmaxf(fmaf(-bfr(mean), cs, tot) * rinv, 0.f);
            if (lane_p < 16) asm volatile("st.shared.u16 [%0], %1;" :: "r"(h1_w), "h"((unsigned short)pack_bf(z, 0.f)) : "memory");
            bar_arrive(NB_H1, 352);
        }
        if (f >= NOCT) return;
        mbar_wait(bars + BAR_CLR * 8);
        unsigned ha = ld_w1(hb0);
        bar_sync(NB_DSENT, 352);
        spin_cycles(dly_d);
        {
            uint4 v[7];
#pragma unroll
            for (int j = 0; j < 7; j++) v[j] = ld_w4(d_src + 128 * j);
#pragma unroll 1
            for (int n = 0; n < SPIN_LIMIT; n++) {
                if (!__any_sync(FULL, (ha & tag) == 0)) break;
                ha = ld_w1(hb0);
            }
            float hs = __uint_as_float(ha);
            hs += __shfl_xor_sync(FULL, hs, 8);
            hs += __shfl_xor_sync(FULL, hs, 16);
            const float base = bfr(xcol + bfr(hs));
            float r = 0.f;
#pragma unroll 1
            for (int n = 0; n < SPIN_LIMIT; n++) {
                float t0 = ((__uint_as_float(v[0].x) + __uint_as_float(v[1].x)) + (__uint_as_float(v[2].x) + __uint_as_float(v[3].x))) +
                           ((__uint_as_float(v[4].x) + __uint_as_float(v[5].x)) + __uint_as_float(v[6].x));
                float t1 = ((__uint_as_float(v[0].y) + __uint_as_float(v[1].y)) + (__uint_as_float(v[2].y) + __uint_as_float(v[3].y))) +
                           ((__uint_as_float(v[4].y) + __uint_as_float(v[5].y)) + __uint_as_float(v[6].y));
                float t2 = ((__uint_as_float(v[0].z) + __uint_as_float(v[1].z)) + (__uint_as_float(v[2].z) + __uint_as_float(v[3].z))) +
                           ((__uint_as_float(v[4].z) + __uint_as_float(v[5].z)) + __uint_as_float(v[6].z));
                float t3 = ((__uint_as_float(v[0].w) + __uint_as_float(v[1].w)) + (__uint_as_float(v[2].w) + __uint_as_float(v[3].w))) +
                           ((__uint_as_float(v[4].w) + __uint_as_float(v[5].w)) + __uint_as_float(v[6].w));
                asm volatile("" : "+f"(t0), "+f"(t1), "+f"(t2), "+f"(t3));
                bool miss = false;
#pragma unroll
                for (int j = 0; j < 7; j++)
                    if (bad4(v[j], tag)) { v[j] = ld_w4(d_src + 128 * j); miss = true; }
                const bool again = __any_sync(FULL, miss);
                r = octet_reduce(t0, t1, t2, t3, lane_p);
                if (!again) break;
            }
            if (lane_p < 8) asm volatile("st.global.u16 [%0], %1;" :: "l"(o_dst), "h"((unsigned short)pack_bf(base + bfr(r), 0.f)) : "memory");
        }
        if (f == 0 && lane == 0) st_w1(scr + PR_EPOCH * PAIR_W, epoch + 1u);
    }
}

unsigned* g_scr_base = nullptr;

}

typedef CUresult (*EncodeTiledFn)(CUtensorMap*, CUtensorMapDataType, cuuint32_t, void*, const cuuint64_t*, const cuuint64_t*,
                                  const cuuint32_t*, const cuuint32_t*, CUtensorMapInterleave, CUtensorMapSwizzle,
                                  CUtensorMapL2promotion, CUtensorMapFloatOOBfill);

extern "C" void kernel_launch(void* const* d_in, const int* in_sizes, int n_in, void* d_out, int out_size) {
    (void)in_sizes; (void)n_in; (void)out_size;
    static EncodeTiledFn encode = nullptr;
    if (!encode) {
        cudaFuncSetAttribute(fk::fused_decode_kernel, cudaFuncAttributeMaxDynamicSharedMemorySize, fk::SMEM_BYTES);
        void* fn = nullptr;
        cudaDriverEntryPointQueryResult qres;
        cudaGetDriverEntryPoint("cuTensorMapEncodeTiled", &fn, cudaEnableDefault, &qres);
        encode = (EncodeTiledFn)fn;
        void* sp = nullptr;
        cudaGetSymbolAddress(&sp, fk::g_scr);
        fk::g_scr_base = (unsigned*)(((uintptr_t)sp + (2u << 20) - 1) & ~(uintptr_t)((2u << 20) - 1));
    }
    CUtensorMap map_v, map_w1, map_wo;
    {
        const cuuint64_t dims[2] = {640, 4096}, strides[1] = {1280};
        const cuuint32_t box[2] = {32, 64}, es[2] = {1, 1};
        encode(&map_wo, CU_TENSOR_MAP_DATA_TYPE_BFLOAT16, 2, d_in[4], dims, strides, box, es, CU_TENSOR_MAP_INTERLEAVE_NONE,
               CU_TENSOR_MAP_SWIZZLE_64B, CU_TENSOR_MAP_L2_PROMOTION_L2_128B, CU_TENSOR_MAP_FLOAT_OOB_FILL_NONE);
    }
    {
        const cuuint64_t dims[2] = {128, 32 * 4096}, strides[1] = {256};
        const cuuint32_t box[2] = {32, 64}, es[2] = {1, 1};
        encode(&map_v, CU_TENSOR_MAP_DATA_TYPE_BFLOAT16, 2, d_in[2], dims, strides, box, es, CU_TENSOR_MAP_INTERLEAVE_NONE,
               CU_TENSOR_MAP_SWIZZLE_64B, CU_TENSOR_MAP_L2_PROMOTION_L2_128B, CU_TENSOR_MAP_FLOAT_OOB_FILL_NONE);
    }
    {
        const cuuint64_t dims[2] = {1728, 640}, strides[1] = {3456};
        const cuuint32_t box[2] = {16, 128}, es[2] = {1, 1};
        encode(&map_w1, CU_TENSOR_MAP_DATA_TYPE_BFLOAT16, 2, d_in[6], dims, strides, box, es, CU_TENSOR_MAP_INTERLEAVE_NONE,
               CU_TENSOR_MAP_SWIZZLE_32B, CU_TENSOR_MAP_L2_PROMOTION_L2_128B, CU_TENSOR_MAP_FLOAT_OOB_FILL_NONE);
    }
    fk::fused_decode_kernel<<<fk::NCTA, fk::NTHREADS, fk::SMEM_BYTES>>>(
        (const __nv_bfloat16*)d_in[0], (const __nv_bfloat16*)d_in[3], (const __nv_bfloat16*)d_in[1],
        (const __nv_bfloat16*)d_in[7], (__nv_bfloat16*)d_out, fk::g_scr_base,
        map_v, map_w1, map_wo);
}
```
